```python
import torch

def _softmax(x, axis=-1):
    return torch.softmax(x, dim=axis)
def _gelu(x):
    return torch.nn.functional.gelu(x, approximate="tanh")
def _silu(x):
    return torch.nn.functional.silu(x)
def _sigmoid(x):
    return torch.sigmoid(x)
def _layernorm(x, axis=-1, eps=1e-5):
    m = x.mean(dim=axis, keepdim=True)
    v = x.var(dim=axis, keepdim=True, unbiased=False)
    return (x - m) / torch.sqrt(v + eps)
def _scatter_add(tgt, idx, src, axis=0):
    return tgt.clone().index_add_(axis, idx, src)
def _segment_sum(src, seg, n):
    out = torch.zeros((n,) + src.shape[1:], dtype=src.dtype)
    return out.index_add_(0, seg, src)
def _pad(x, pw):
    flat = tuple(v for pair in reversed(pw) for v in pair)
    return torch.nn.functional.pad(x, flat)

kernel_name = 'recurrent_scan__sliding_block_cached__dense_activation_squared_relu__decode'

def setup_inputs():

    _w = (lambda a: (lambda t: t.to(torch.bfloat16) if t.is_floating_point() else t)(torch.as_tensor(a)))
    def _A_setup():
        B, Sq, D = 2, 1, 640
        Hq, Hkv, Sk, Dh = 32, 32, 8192, 192
        assert Hq % Hkv == 0, (Hq, Hkv)
        return {
            "x": _w((lambda *s: torch.randn(*s, dtype=torch.bfloat16) * 0.05)(B, Sq, D)),
            "k_cache": _w((lambda *s: torch.randn(*s, dtype=torch.bfloat16) * 0.8)(B, Hkv, Sk, Dh)),
            "v_cache": _w((lambda *s: torch.randn(*s, dtype=torch.bfloat16) * 0.2)(B, Hkv, Sk, Dh)),
            "wq": _w((lambda *s: torch.randn(*s, dtype=torch.bfloat16) * 0.8)(D, Hq * Dh) * (D ** -0.5)),
            "wo": _w((lambda *s: torch.randn(*s, dtype=torch.bfloat16) * 0.2)(Hq * Dh, D) * ((Hq * Dh) ** -0.5)),
        }
    _A_in = _A_setup()

    def _B_setup():
        B, S, D, F = 2, 1, 640, 1536
        return {
            "x": _w((lambda *s: torch.randn(*s, dtype=torch.bfloat16) * 0.05)(B, S, D)),
            "w1": _w((lambda *s: torch.randn(*s, dtype=torch.bfloat16) * 0.1)(D, F)),
            "b1": _w((lambda *s: torch.randn(*s, dtype=torch.bfloat16) * 0.8)(F)),
            "w2": _w((lambda *s: torch.randn(*s, dtype=torch.bfloat16) * 0.1)(F, D)),
            "b2": _w((lambda *s: torch.randn(*s, dtype=torch.bfloat16) * 12.8)(D)),
        }
    _B_in = _B_setup()

    return {
        "A_x": _A_in["x"],
        "A_k_cache": _A_in["k_cache"],
        "A_v_cache": _A_in["v_cache"],
        "A_wq": _A_in["wq"],
        "A_wo": _A_in["wo"],
        "B_x": _B_in["x"],
        "B_w1": _B_in["w1"],
        "B_b1": _B_in["b1"],
        "B_w2": _B_in["w2"],
        "B_b2": _B_in["b2"],
    }

def reference(A_x, A_k_cache, A_v_cache, A_wq, A_wo, B_x, B_w1, B_b1, B_w2, B_b2):
    def _A_ref(x, k_cache, v_cache, wq, wo):
        B, Sq, D = x.shape
        Hq, Dh = 32, 192
        Hkv, Sk = k_cache.shape[1], k_cache.shape[2]
        W = min(4096, max(256, Sk // 4))
        rep = Hq // Hkv
        q = (lambda x, *d: x.permute(*d))((x @ wq).reshape(B, Sq, Hq, Dh), 0, 2, 1, 3)
        k = (lambda x, n, axis: torch.repeat_interleave(x, n, dim=axis))(k_cache[:, :, Sk - W:, :], rep, axis=1)
        v = (lambda x, n, axis: torch.repeat_interleave(x, n, dim=axis))(v_cache[:, :, Sk - W:, :], rep, axis=1)
        scores = torch.einsum("bhqd,bhkd->bhqk", q, k) * (Dh ** -0.5)
        p = _softmax(scores, axis=-1)
        o = torch.einsum("bhqk,bhkd->bhqd", p, v)
        return (lambda x, *d: x.permute(*d))(o, 0, 2, 1, 3).reshape(B, Sq, Hq * Dh) @ wo

    def _B_ref(x, w1, b1, w2, b2):
        h = torch.einsum("bsd,df->bsf", x, w1) + b1
        zero = torch.zeros_like(h)
        r = torch.where(h > zero, h, zero)
        h = r * r
        out = torch.einsum("bsf,fd->bsd", h, w2) + b2
        return out

    x = A_x
    xn = _layernorm(x, axis=-1)
    s = _A_ref(xn, A_k_cache, A_v_cache, A_wq, A_wo)
    g = _silu(_B_ref(xn, B_w1, B_b1, B_w2, B_b2))
    return x + s * g
```

```cpp
#include <cuda.h>
#include <cuda_runtime.h>
#include <cuda_bf16.h>
#include <stdint.h>

namespace {

constexpr int D = 640, DH = 192, SK = 8192, WIN = 2048, FF = 1536, QD = 6144;
constexpr int NCTA = 128, NTHR = 352;
constexpr int TILE = 12288;
constexpr int NS = 16;
#define DEPTH_ 7
#define DEPTH_TAIL_ 8
#define BURST_ (2 * TILE)
#define PACE_GBS 3175.0
constexpr int BURST = BURST_;
constexpr int DEPTH = DEPTH_;
constexpr int DEPTH_TAIL = DEPTH_TAIL_;
constexpr int V_WQ = 0, V_W1 = 5, V_K = 7, V_V = 39, V_W2 = 71, V_WO = 73, NT = 79;
constexpr int WT = 6 * D * 2;
constexpr int OT = 8 * D * 2;
#define QPOLL_NS 200
#define NPRE 2
#define TAIL_I0 NT
#define TAIL_PCT 100
#define GATE_T 77
#define GATE_NS 100
#define ROT 3
#define POLL_NS 150
constexpr int XS = 224;
constexpr unsigned SPIN_LIMIT = 1u << 20;

constexpr int SM_RING = 0;
constexpr int SM_RED  = SM_RING + NS * TILE;
constexpr int SM_P    = SM_RED + 2 * 8 * 384 * 4;
constexpr int SM_Q    = SM_P + 8 * 128 * 4;
constexpr int SM_CO   = SM_Q + 384 * 4;
constexpr int SM_MX   = SM_CO + 128 * 2;
constexpr int SM_FIN  = SM_MX + 32 * 4;
constexpr int SM_BAR  = SM_FIN + 128 * 4;
constexpr int SM_TOTAL = SM_BAR + (2 * NS + 6) * 8;

__device__ float4 g_q[NCTA * 96];
__device__ float4 g_h[NCTA * 96];
__device__ float  g_o[2 * NCTA * XS];
__device__ float4 g_fp[NCTA * 320];
__device__ float4 g_sp[NCTA * 320];
__device__ unsigned g_epoch;
#define STAMP(i) do {} while (0)
#define ARR(i) do {} while (0)
#define PROF_BEGIN
#define PROF_END do {} while (0)

struct Params {
    const __nv_bfloat16 *x, *k, *v, *b1, *b2, *w2, *wo;
    __nv_bfloat16* out;
    uint32_t tstart;
    uint32_t pace;
};

__device__ __forceinline__ void mbar_init(uint32_t a, int cnt) {
    asm volatile("mbarrier.init.shared::cta.b64 [%0], %1;" ::"r"(a), "r"(cnt) : "memory");
}
__device__ __forceinline__ void mbar_expect(uint32_t a, uint32_t bytes) {
    asm volatile("mbarrier.arrive.expect_tx.shared::cta.b64 _, [%0], %1;" ::"r"(a), "r"(bytes) : "memory");
}
__device__ __forceinline__ void mbar_arrive(uint32_t a) {
    asm volatile("mbarrier.arrive.shared::cta.b64 _, [%0];" ::"r"(a) : "memory");
}
__device__ __forceinline__ void mbar_wait(uint32_t a, uint32_t parity, unsigned& n) {
    asm volatile(
        "{\n.reg .pred p, q;\n"
        "W_%=:\n"
        ".pragma \"nounroll\";\n"
        "mbarrier.try_wait.parity.shared::cta.b64 p, [%1], %2;\n"
        "@!p add.u32 %0, %0, 1;\n"
        "setp.lt.and.u32 q, %0, %3, !p;\n"
        "@q bra W_%=;\n}"
        : "+r"(n) : "r"(a), "r"(parity), "n"(SPIN_LIMIT) : "memory");
}
__device__ __forceinline__ uint32_t gtime32() {
    uint32_t t;
    asm volatile("mov.u32 %0, %%globaltimer_lo;" : "=r"(t) :: "memory");
    return t;
}
__host__ __device__ constexpr int vof(int i) { return i < NPRE ? V_K + i : i < V_K + NPRE ? i - NPRE : i; }
__host__ __device__ constexpr int tile_bytes(int v) { return (v < V_W1 || (v >= V_K && v < V_W2)) ? TILE : v < V_WO ? WT : OT; }
__host__ __device__ constexpr int issued_before(int i) {
    return i <= NPRE + 5 ? i * TILE : i <= NPRE + 7 ? (NPRE + 5) * TILE + (i - NPRE - 5) * WT : i <= V_W2 ? 2 * WT + (i - 2) * TILE
         : i <= V_WO ? 2 * WT + (V_W2 - 2) * TILE + (i - V_W2) * WT : 4 * WT + (V_W2 - 2) * TILE + (i - V_WO) * OT;
}
__host__ __device__ constexpr int sched_pos(int i) {
    return (i <= TAIL_I0 ? issued_before(i) - BURST
                         : issued_before(TAIL_I0) - BURST + (issued_before(i) - issued_before(TAIL_I0)) / 100 * TAIL_PCT) / 256;
}
__device__ __forceinline__ void mbar_sleep(uint32_t a, unsigned& n) {
    asm volatile(
        "{\n.reg .pred p;\n"
        "W_%=:\n"
        ".pragma \"nounroll\";\n"
        "mbarrier.try_wait.parity.shared::cta.b64 p, [%1], 0, %3;\n"
        "@p bra D_%=;\n"
        "add.u32 %0, %0, 64;\n"
        "setp.lt.u32 p, %0, %2;\n"
        "@p bra W_%=;\n"
        "D_%=:\n}"
        : "+r"(n) : "r"(a), "n"(SPIN_LIMIT), "r"(100000) : "memory");
}
__device__ __forceinline__ bool elect_one() {
    uint32_t r;
    asm volatile("{\n.reg .pred p;\nelect.sync _|p, 0xffffffff;\nselp.u32 %0, 1, 0, p;\n}" : "=r"(r));
    return r;
}
__device__ __forceinline__ void bulk_load(uint32_t dst, const void* src, uint32_t bytes, uint32_t mbar, uint64_t pol) {
    asm volatile("cp.async.bulk.shared::cluster.global.mbarrier::complete_tx::bytes.L2::cache_hint [%0], [%1], %2, [%3], %4;"
                 ::"r"(dst), "l"(src), "r"(bytes), "r"(mbar), "l"(pol) : "memory");
}
__device__ __forceinline__ void box_load(uint32_t dst, const CUtensorMap* map, int col, int row, uint32_t mbar, uint64_t pol) {
    asm volatile("cp.async.bulk.tensor.2d.shared::cluster.global.mbarrier::complete_tx::bytes.L2::cache_hint [%0], [%1, {%2, %3}], [%4], %5;"
                 ::"r"(dst), "l"(map), "r"(col), "r"(row), "r"(mbar), "l"(pol) : "memory");
}
__device__ __forceinline__ void box3_load(uint32_t dst, const CUtensorMap* map, int row, uint32_t mbar, uint64_t pol) {
    asm volatile("cp.async.bulk.tensor.3d.shared::cluster.global.mbarrier::complete_tx::bytes.L2::cache_hint [%0], [%1, {0, %2, 0}], [%3], %4;"
                 ::"r"(dst), "l"(map), "r"(row), "r"(mbar), "l"(pol) : "memory");
}
__device__ __forceinline__ void wbox_load(uint32_t dst, const CUtensorMap* map, int row, uint32_t mbar, uint64_t pol) {
    box3_load(dst, map, row, mbar, pol);
}
#define WLINE(w, r, R) ((w) * (R) + (r))
__device__ __forceinline__ bool mbar_test(uint32_t a, uint32_t parity) {
    uint32_t ok;
    asm volatile("{\n.reg .pred p;\nmbarrier.test_wait.parity.shared::cta.b64 p, [%1], %2;\nselp.u32 %0, 1, 0, p;\n}"
                 : "=r"(ok) : "r"(a), "r"(parity) : "memory");
    return ok;
}
__device__ __forceinline__ uint32_t wfrag_addr(uint32_t line, int mi) { return line + ((mi ^ ((line >> 7) & 7)) << 4); }
__device__ __forceinline__ void load_wfrag(uint32_t (&a)[8], uint32_t addr) {
    asm volatile("ldmatrix.sync.aligned.m8n8.x4.trans.shared.b16 {%0,%1,%2,%3}, [%4];"
                 : "=r"(a[0]), "=r"(a[1]), "=r"(a[2]), "=r"(a[3]) : "r"(addr) : "memory");
    asm volatile("ldmatrix.sync.aligned.m8n8.x4.trans.shared.b16 {%0,%1,%2,%3}, [%4];"
                 : "=r"(a[4]), "=r"(a[5]), "=r"(a[6]), "=r"(a[7]) : "r"(addr ^ 64) : "memory");
}
__device__ __forceinline__ void mma_w(float4 (&d)[4], const uint32_t (&a)[8], uint32_t b) {
#pragma unroll
    for (int m = 0; m < 4; m++)
        asm volatile("mma.sync.aligned.m16n8k8.row.col.f32.bf16.bf16.f32 {%0,%1,%2,%3}, {%4,%5}, {%6}, {%0,%1,%2,%3};"
                     : "+f"(d[m].x), "+f"(d[m].y), "+f"(d[m].z), "+f"(d[m].w) : "r"(a[2 * m]), "r"(a[2 * m + 1]), "r"(b));
}
__device__ __forceinline__ void bar_sync(int id, int cnt) { asm volatile("bar.sync %0, %1;" ::"r"(id), "r"(cnt) : "memory"); }
__device__ __forceinline__ void bar_arrive(int id, int cnt) { asm volatile("bar.arrive %0, %1;" ::"r"(id), "r"(cnt) : "memory"); }

__device__ __forceinline__ uint4 lds128(uint32_t a) {
    uint4 v;
    asm volatile("ld.shared.v4.u32 {%0,%1,%2,%3}, [%4];" : "=r"(v.x), "=r"(v.y), "=r"(v.z), "=r"(v.w) : "r"(a) : "memory");
    return v;
}
__device__ __forceinline__ float4 lds128f(uint32_t a) {
    float4 v;
    asm volatile("ld.shared.v4.f32 {%0,%1,%2,%3}, [%4];" : "=f"(v.x), "=f"(v.y), "=f"(v.z), "=f"(v.w) : "r"(a) : "memory");
    return v;
}
__device__ __forceinline__ uint32_t lds32(uint32_t a) {
    uint32_t v;
    asm volatile("ld.shared.u32 %0, [%1];" : "=r"(v) : "r"(a) : "memory");
    return v;
}
__device__ __forceinline__ uint32_t tagw(float v, uint32_t tag) { return (__float_as_uint(v) & ~3u) | tag; }
__device__ __forceinline__ void st_tag4(float4* p, float4 v, uint32_t tag) {
    asm volatile("st.relaxed.gpu.global.v4.u32 [%0], {%1,%2,%3,%4};"
                 ::"l"(p), "r"(tagw(v.x, tag)), "r"(tagw(v.y, tag)), "r"(tagw(v.z, tag)), "r"(tagw(v.w, tag)) : "memory");
}
__device__ __forceinline__ void st_tag1(float* p, float v, uint32_t tag) {
    asm volatile("st.relaxed.gpu.global.u32 [%0], %1;" ::"l"(p), "r"(tagw(v, tag)) : "memory");
}
__device__ __forceinline__ void st_zero4(void* p) {
    asm volatile("st.relaxed.gpu.global.v4.u32 [%0], {%1,%1,%1,%1};" ::"l"(p), "r"(0) : "memory");
}
__device__ __forceinline__ uint32_t next_tag() {
    uint32_t e;
    asm volatile("ld.relaxed.gpu.global.u32 %0, [%1];" : "=r"(e) : "l"(&g_epoch) : "memory");
    return e == 3 ? 1 : e + 1;
}
__device__ __forceinline__ uint4 ld_x4(const void* p) {
    uint4 v;
    asm volatile("ld.relaxed.gpu.global.v4.u32 {%0,%1,%2,%3}, [%4];" : "=r"(v.x), "=r"(v.y), "=r"(v.z), "=r"(v.w) : "l"(p) : "memory");
    return v;
}
__device__ __forceinline__ uint2 ld_x2(const float* p) {
    uint2 v;
    asm volatile("ld.relaxed.gpu.global.v2.u32 {%0,%1}, [%2];" : "=r"(v.x), "=r"(v.y) : "l"(p) : "memory");
    return v;
}
__device__ __forceinline__ uint32_t ld_x1(const float* p) {
    uint32_t v;
    asm volatile("ld.relaxed.gpu.global.u32 %0, [%1];" : "=r"(v) : "l"(p) : "memory");
    return v;
}
__device__ __forceinline__ uint32_t take1(float* p, bool want) {
    uint32_t t;
    asm volatile("{\n.reg .pred q;\nsetp.ne.u32 q, %2, 0;\nmov.u32 %0, 0;\n@q atom.relaxed.gpu.global.exch.b32 %0, [%1], 0;\n}"
                 : "=r"(t) : "l"(p), "r"((uint32_t)want) : "memory");
    return t;
}
__device__ __forceinline__ uint4 take4(float4* p, bool want) {
    uint4 t;
    asm volatile("{\n.reg .pred q;\n.reg .b128 x;\n.reg .b64 lo, hi;\nsetp.ne.u32 q, %5, 0;\nmov.b64 lo, 0;\nmov.b128 x, {lo, lo};\n"
                 "@q atom.relaxed.gpu.global.exch.b128 x, [%4], x;\nmov.b128 {lo, hi}, x;\n"
                 "mov.b64 {%0, %1}, lo;\nmov.b64 {%2, %3}, hi;\n}"
                 : "=r"(t.x), "=r"(t.y), "=r"(t.z), "=r"(t.w) : "l"(p), "r"((uint32_t)want) : "memory");
    return t;
}
__device__ __forceinline__ void reload4(uint4& v, const float4* p, bool want) {
    asm volatile("{\n.reg .pred q;\nsetp.ne.u32 q, %5, 0;\n@q ld.relaxed.gpu.global.v4.u32 {%0,%1,%2,%3}, [%4];\n}"
                 : "+r"(v.x), "+r"(v.y), "+r"(v.z), "+r"(v.w) : "l"(p), "r"((uint32_t)want) : "memory");
}
__device__ __forceinline__ void st_pkt(const float4* p, float4 v, uint32_t tag) {
    asm volatile("{\n.reg .b128 x;\n.reg .b64 lo, hi;\nmov.b64 lo, {%1, %2};\nmov.b64 hi, {%3, %4};\nmov.b128 x, {lo, hi};\n"
                 "st.relaxed.gpu.global.b128 [%0], x;\n}"
                 ::"l"(p), "r"(tagw(v.x, tag)), "r"(__float_as_uint(v.y)), "r"(__float_as_uint(v.z)), "r"(__float_as_uint(v.w)) : "memory");
}
__device__ __forceinline__ void ld_pkt(uint4& v, const float4* p, bool want) {
    asm volatile("{\n.reg .pred q;\n.reg .b128 x;\n.reg .b64 lo, hi;\nsetp.ne.u32 q, %5, 0;\n"
                 "mov.b64 lo, {%0, %1};\nmov.b64 hi, {%2, %3};\nmov.b128 x, {lo, hi};\n"
                 "@q ld.relaxed.gpu.global.b128 x, [%4];\n"
                 "mov.b128 {lo, hi}, x;\nmov.b64 {%0, %1}, lo;\nmov.b64 {%2, %3}, hi;\n}"
                 : "+r"(v.x), "+r"(v.y), "+r"(v.z), "+r"(v.w) : "l"(p), "r"((uint32_t)want) : "memory");
}
__device__ __forceinline__ bool bad_pkt(const uint4& v, uint32_t tag) { return (v.x & 3u) != tag; }
template <class T> __device__ __forceinline__ void pin(T*& p) { asm volatile("" : "+l"(p)); }
__device__ __forceinline__ void pin(uint32_t& v) { asm volatile("" : "+r"(v)); }
__device__ __forceinline__ void keep1(uint32_t& v, uint32_t t, uint32_t tag) { v = (t & 3u) == tag ? t : v; }
__device__ __forceinline__ void keep4(uint4& v, uint4 t, uint32_t tag) {
    keep1(v.x, t.x, tag); keep1(v.y, t.y, tag); keep1(v.z, t.z, tag); keep1(v.w, t.w, tag);
}
__device__ __forceinline__ uint32_t bad4(uint4 v, uint32_t tag) { return ((v.x ^ tag) | (v.y ^ tag) | (v.z ^ tag) | (v.w ^ tag)) & 3u; }
__device__ __forceinline__ float4 asf4(uint4 v) {
    return make_float4(__uint_as_float(v.x), __uint_as_float(v.y), __uint_as_float(v.z), __uint_as_float(v.w));
}
__device__ __forceinline__ float bf_lo(uint32_t w) { return __uint_as_float(w << 16); }
__device__ __forceinline__ float bf_hi(uint32_t w) { return __uint_as_float(w & 0xffff0000u); }
__device__ __forceinline__ float rbf(float v) { return __bfloat162float(__float2bfloat16_rn(v)); }

__device__ __forceinline__ float fin_reduce(float4 a, int lane) {
    const bool h4 = lane & 16, h3 = lane & 8;
    float s0 = h4 ? a.x : a.z, s1 = h4 ? a.y : a.w;
    float k0 = h4 ? a.z : a.x, k1 = h4 ? a.w : a.y;
    k0 += __shfl_xor_sync(~0u, s0, 16);
    k1 += __shfl_xor_sync(~0u, s1, 16);
    float s = h3 ? k0 : k1, k = h3 ? k1 : k0;
    k += __shfl_xor_sync(~0u, s, 8);
    k += __shfl_xor_sync(~0u, k, 4);
    return k;
}

__global__ void __launch_bounds__(NTHR, 1)
fused_decode_kernel(const __grid_constant__ CUtensorMap map_wq, const __grid_constant__ CUtensorMap map_w1,
                    const __grid_constant__ CUtensorMap map_w2, const __grid_constant__ CUtensorMap map_wo, const Params p) {
    extern __shared__ __align__(1024) unsigned char smem[];
    const uint32_t sb = (uint32_t)__cvta_generic_to_shared(smem);
    const int tid = threadIdx.x >= 32 ? (int)threadIdx.x - 32 : (int)threadIdx.x + 320, lane = tid & 31;
    const int warp = tid >> 5;
    const int c = blockIdx.x, h = c >> 2, j = c & 3;
    const uint32_t full0 = sb + SM_BAR, empty0 = full0 + NS * 8, bar_hh = empty0 + NS * 8, bar_oc = bar_hh + 8;
    const uint32_t go_q = bar_hh + 16, go_mid = bar_hh + 24, go_end = bar_hh + 32, go_st = bar_hh + 40;
    float* s_mx = reinterpret_cast<float*>(smem + SM_MX);
    __nv_bfloat16* s_co = reinterpret_cast<__nv_bfloat16*>(smem + SM_CO);
    unsigned it = 0;
    PROF_BEGIN

    uint64_t pol;
    asm volatile("createpolicy.fractional.L2::evict_first.b64 %0, 1.0;" : "=l"(pol));
    const size_t kvoff = (size_t)(uint32_t)((h * SK + (SK - WIN)) * (DH * 2) + j * TILE);
    const char* kb = reinterpret_cast<const char*>(p.k) + kvoff;
    const int rot = (h * ROT) & 15;
    uint32_t t0 = 0;
    if (threadIdx.x < 32) {
        if (elect_one()) {
#pragma unroll
            for (int i = 0; i < 2; i++) {
                const int v = vof(i);
                mbar_init(full0 + 8 * v, 1);
                mbar_expect(full0 + 8 * v, TILE);
                if (v >= V_K) bulk_load(sb + SM_RING + v * TILE, kb + ((i + rot) & 15) * (4 * TILE), TILE, full0 + 8 * v, pol);
                else box_load(sb + SM_RING + v * TILE, &map_wq, h * DH, 160 * j + 32 * v, full0 + 8 * v, pol);
            }
        }
        t0 = gtime32();
        __syncwarp();
    }
    if (threadIdx.x < 32) {
        const bool leader = elect_one();
        if (leader) {
            STAMP(0);
            if (NPRE >= 2) asm volatile("prefetch.tensormap [%0];" ::"l"(&map_wq) : "memory");
            asm volatile("prefetch.tensormap [%0];" ::"l"(&map_w1) : "memory");
#pragma unroll
            for (int s = 0; s < NS; s++) {
                if (s != vof(0) && s != vof(1)) mbar_init(full0 + 8 * s, 1);
                mbar_init(empty0 + 8 * s, 8);
            }
#pragma unroll
            for (int s = 0; s < 6; s++) mbar_init(bar_hh + 8 * s, s < 2 ? 2 : 1);
        }
        __syncwarp();
        bar_arrive(1, NTHR);
        uint32_t epoch;
        asm volatile("ld.relaxed.gpu.global.u32 %0, [%1];" : "=r"(epoch) : "l"(&g_epoch) : "memory");
        const int fu = 4 * c + (lane & 3), fb = (lane >> 3) & 1;
        const int fcol = (fu >> 3) * 16 + (fu & 7) + ((lane >> 4) << 3);
        unsigned short xo16 = 0, b216 = 0;
        if (c < 80) {
            asm volatile("ld.volatile.global.u16 %0, [%1];" : "=h"(xo16) : "l"(p.x + fb * D + fcol) : "memory");
            asm volatile("ld.volatile.global.u16 %0, [%1];" : "=h"(b216) : "l"(p.b2 + fcol) : "memory");
        }
        __syncwarp();
        if (leader) {
            const char* vb = reinterpret_cast<const char*>(p.v) + kvoff;
            asm volatile("prefetch.tensormap [%0];" ::"l"(&map_w2) : "memory");
            asm volatile("prefetch.tensormap [%0];" ::"l"(&map_wo) : "memory");
            constexpr size_t bstride = (size_t)32 * SK * DH * 2;
#pragma unroll
            for (int i = 2; i < NT; i++) {
                const int v = vof(i);
                const uint32_t slot = v & (NS - 1), fbar = full0 + 8 * slot, dst = sb + SM_RING + slot * TILE;
                const uint32_t bytes = tile_bytes(v);
                const int u = v - V_K;
                const char* kvsrc = ((u & 32) ? vb : kb) + (((u & 16) ? bstride : 0) + (uint32_t)((u + rot) & 15) * (4 * TILE));
                if (v >= V_K && v < V_W2) asm volatile("" : "+l"(kvsrc));
                if (v >= NS) mbar_wait(empty0 + 8 * slot, ((v / NS) & 1) ^ 1, it);
                mbar_expect(fbar, bytes);
                if (issued_before(i) >= BURST) {
                    const uint32_t due = p.tstart + ((uint32_t)(sched_pos(i) * p.pace) >> 16);
                    while (gtime32() - t0 < due) {}
                }
                const int d = i - (i < V_W2 ? DEPTH : DEPTH_TAIL);
                if (d >= 0) {
                    const int dv = vof(d);
                    mbar_wait(full0 + 8 * (dv & (NS - 1)), (dv / NS) & 1, it);
                }
                if (v < V_W1) box_load(dst, &map_wq, h * DH, 160 * j + 32 * v, fbar, pol);
                else if (v < V_K) box_load(dst, &map_w1, (c & 7) * DH, 40 * (c >> 3) + 20 * (v - V_W1), fbar, pol);
                else if (v < V_W2) {
                    bulk_load(dst, kvsrc, TILE, fbar, pol);
                }
                else if (v < V_WO) wbox_load(dst, &map_w2, c * 12 + (v - V_W2) * 6, fbar, pol);
                else wbox_load(dst, &map_wo, c * 48 + (v - V_WO) * 8, fbar, pol);
            }
            STAMP(1);
        }
        __syncwarp();
        const uint32_t tag = epoch == 3 ? 1 : epoch + 1;
        const float xo = bf_lo(xo16), b2v = bf_lo(b216);
        if (c < 80) {
            if (GATE_T) mbar_wait(full0 + 8 * (GATE_T & (NS - 1)), (GATE_T / NS) & 1, it);
            const float4* pf = g_fp + (lane >> 2) * 320 + fu;
            uint4 v[16];
#pragma unroll
            for (int k = 0; k < 16; k++) v[k] = make_uint4(0, 0, 0, 0);
#pragma unroll 1
            while (true) {
#pragma unroll
                for (int k = 0; k < 16; k++) ld_pkt(v[k], pf + k * 8 * 320, bad_pkt(v[k], tag));
                bool bad = false;
#pragma unroll
                for (int k = 0; k < 16; k++) bad |= bad_pkt(v[k], tag);
                if (!__any_sync(~0u, bad) || ++it >= SPIN_LIMIT) break;
                if (GATE_NS) __nanosleep(GATE_NS);
            }
            float4 a = asf4(v[0]);
#pragma unroll
            for (int k = 1; k < 16; k++) { const float4 t = asf4(v[k]); a.x += t.x; a.y += t.y; a.z += t.z; a.w += t.w; }
            const float f = rbf(rbf(fin_reduce(a, lane)) + b2v);
            const float gate = rbf(__fdividef(f, 1.f + __expf(-f)));
            if (lane == 0) STAMP(12);
            __nv_bfloat16* dst = p.out + fb * D + fcol;
            uint32_t fa = sb + SM_FIN + ((lane >> 3) * 4 + (lane & 3)) * 32;
            pin(dst); pin(fa);
            bar_sync(9, 288);
            const float4 u = lds128f(fa), w = lds128f(fa + 16);
            const float s = ((u.x + u.y) + (u.z + u.w)) + ((w.x + w.y) + (w.z + w.w));
            if (!(lane & 4)) *dst = __float2bfloat16_rn(xo + rbf(rbf(s) * gate));
            if (c == 0 && lane == 0) asm volatile("st.relaxed.gpu.global.u32 [%0], %1;" ::"l"(&g_epoch), "r"(tag) : "memory");
            if (lane == 0) STAMP(9);
        }
        PROF_END;
        return;
    }

    uint32_t tag;
    if (warp >= 8) {
        if (warp == 8) {
#pragma unroll 1
            for (int i = lane; i < 96; i += 32) {
                st_zero4(&g_q[c * 96 + i]); st_zero4(&g_h[c * 96 + i]);
            }
            tag = next_tag();
            __syncwarp();
            bar_sync(1, NTHR);
            mbar_sleep(go_mid, it);
#pragma unroll 1
            for (int i = lane; i < 320; i += 32) { st_zero4(&g_fp[c * 320 + i]); st_zero4(&g_sp[c * 320 + i]); }
#pragma unroll 1
            for (int i = lane; i < 48; i += 32) st_zero4(&g_o[(NCTA + c) * XS + i * 4]);
        } else {
            const int fb = lane >= 12, ff = lane - fb * 12;
            float b1v = 0.f;
            if (lane < 24) b1v = __bfloat162float(p.b1[c * 12 + ff]);
            tag = next_tag();
            bar_sync(1, NTHR);
            mbar_sleep(go_q, it);
            if (lane < 24) {
                const float* src = reinterpret_cast<const float*>(g_h + (c >> 4) * 96) + ((c & 15) * 12 + ff) * 2 + fb;
                uint32_t v[16], bad;
#pragma unroll 1
                do {
                    bad = 0;
#pragma unroll
                    for (int r = 0; r < 16; r++) v[r] = ld_x1(src + r * 8 * 384);
#pragma unroll
                    for (int r = 0; r < 16; r++) bad |= (v[r] ^ tag) & 3u;
                    if (bad) __nanosleep(200);
                } while (bad && ++it < SPIN_LIMIT);
                float s = 0.f;
#pragma unroll
                for (int r = 0; r < 16; r++) s += __uint_as_float(v[r]);
                float hv = rbf(rbf(s) + b1v);
                hv = hv > 0.f ? hv : 0.f;
                s_co[fb * 64 + ff + (ff >= 6 ? 2 : 0)] = __float2bfloat16_rn(hv * hv);
            } else {
                s_co[(lane & 1) * 64 + (lane & 2) * 4 + 6 + ((lane >> 2) & 1)] = __float2bfloat16_rn(0.f);
            }
        }
        __syncwarp();
        if (lane == 0) mbar_arrive(bar_hh);
        {
            const int b = warp - 8;
            float* src = g_o + (b * NCTA + h * 4) * XS;
            mbar_sleep(go_st, it);
            uint32_t sv = 0;
            if (lane < 8) {
#pragma unroll 1
                do { sv = take1(src + (lane >> 1) * XS + 192 + 2 * j + (lane & 1), true); } while ((sv & 3u) != tag && ++it < SPIN_LIMIT);
            }
            __syncwarp();
            float f[4], dn = 0.f;
#pragma unroll
            for (int k = 0; k < 4; k++) f[k] = __uint_as_float(__shfl_sync(~0u, sv, 2 * k));
            const float m = fmaxf(fmaxf(f[0], f[1]), fmaxf(f[2], f[3]));
#pragma unroll
            for (int k = 0; k < 4; k++) {
                f[k] = __expf(f[k] - m);
                dn = fmaf(f[k], __uint_as_float(__shfl_sync(~0u, sv, 2 * k + 1)), dn);
            }
#pragma unroll
            for (int k = 0; k < 4; k++) f[k] = __fdividef(f[k], dn);
            if (b == 1) mbar_sleep(go_end, it);
            src += 48 * j + lane;
            uint32_t o0[4] = {0, 0, 0, 0}, o1[4] = {tag, tag, tag, tag}, bad;
            if (lane < 16) o1[0] = o1[1] = o1[2] = o1[3] = 0;
#pragma unroll 1
            do {
                bad = 0;
                uint32_t t0[4], t1[4];
#pragma unroll
                for (int k = 0; k < 4; k++) {
                    t0[k] = take1(src + k * XS, (o0[k] & 3u) != tag);
                    t1[k] = take1(src + k * XS + 32, (o1[k] & 3u) != tag);
                }
#pragma unroll
                for (int k = 0; k < 4; k++) {
                    keep1(o0[k], t0[k], tag); keep1(o1[k], t1[k], tag);
                    bad |= ((o0[k] ^ tag) | (o1[k] ^ tag)) & 3u;
                }
            } while (bad && ++it < SPIN_LIMIT);
            float n0 = 0.f, n1 = 0.f;
#pragma unroll
            for (int k = 0; k < 4; k++) {
                n0 = fmaf(f[k], __uint_as_float(o0[k]), n0);
                n1 = fmaf(f[k], __uint_as_float(o1[k]), n1);
            }
            s_co[b * 64 + 16 + lane] = __float2bfloat16_rn(n0);
            if (lane < 16) s_co[b * 64 + 48 + lane] = __float2bfloat16_rn(n1);
            __syncwarp();
            if (lane == 0) { mbar_arrive(bar_oc); if (b == 1) STAMP(7); }
            if (b == 0) mbar_sleep(go_end, it);
        }
    } else {
        const int g = lane >> 3, jj = lane & 7;
        const uint32_t pbase = sb + SM_P + warp * 512;
        {
            uint2 xr[2][5];
#pragma unroll
            for (int b = 0; b < 2; b++)
#pragma unroll
                for (int k = 0; k < 5; k++)
                    xr[b][k] = __ldg(reinterpret_cast<const uint2*>(p.x + b * D) + lane + 32 * k);
            const int row = jj < 5 ? 160 * j + 32 * jj + 4 * warp + g
                                   : (jj < 7 && warp < 5 ? 40 * (c >> 3) + 20 * (jj - 5) + 4 * warp + g : 0);
            const float x0 = __bfloat162float(p.x[row]), x1 = __bfloat162float(p.x[D + row]);
            tag = next_tag();
            float mean[2], den[2];
#pragma unroll
            for (int b = 0; b < 2; b++) {
                float s = 0.f;
#pragma unroll
                for (int k = 0; k < 5; k++)
                    s += (bf_lo(xr[b][k].x) + bf_hi(xr[b][k].x)) + (bf_lo(xr[b][k].y) + bf_hi(xr[b][k].y));
                mean[b] = s;
            }
#pragma unroll
            for (int o = 16; o; o >>= 1) {
                mean[0] += __shfl_xor_sync(~0u, mean[0], o);
                mean[1] += __shfl_xor_sync(~0u, mean[1], o);
            }
#pragma unroll
            for (int b = 0; b < 2; b++) {
                mean[b] *= (1.f / D);
                float s = 0.f;
#pragma unroll
                for (int k = 0; k < 5; k++) {
                    const float d0 = bf_lo(xr[b][k].x) - mean[b], d1 = bf_hi(xr[b][k].x) - mean[b];
                    const float d2 = bf_lo(xr[b][k].y) - mean[b], d3 = bf_hi(xr[b][k].y) - mean[b];
                    s = fmaf(d0, d0, fmaf(d1, d1, fmaf(d2, d2, fmaf(d3, d3, s))));
                }
                den[b] = s;
            }
#pragma unroll
            for (int o = 16; o; o >>= 1) {
                den[0] += __shfl_xor_sync(~0u, den[0], o);
                den[1] += __shfl_xor_sync(~0u, den[1], o);
            }
#pragma unroll
            for (int b = 0; b < 2; b++) {
                float sq;
                asm("sqrt.approx.f32 %0, %1;" : "=f"(sq) : "f"(rbf(rbf(den[b] * (1.f / D)) + 1e-5f)));
                den[b] = rbf(sq);
                mean[b] = rbf(mean[b]);
            }
            reinterpret_cast<float2*>(smem + SM_P + warp * 512)[jj * 4 + g] =
                make_float2(rbf(__fdividef(rbf(x0 - mean[0]), den[0])), rbf(__fdividef(rbf(x1 - mean[1]), den[1])));
        }
        bar_sync(1, NTHR);
        if (tid == 0) STAMP(10);
        const uint32_t wordoff = sb + SM_RING + warp * 4 * 384 + lane * 4;
#pragma unroll
        for (int kind = 0; kind < 2; kind++) {
            float acc[12];
#pragma unroll
            for (int e = 0; e < 12; e++) acc[e] = 0.f;
#pragma unroll 1
            for (int v = kind ? V_W1 : V_WQ; v < (kind ? V_K : V_W1); v++) {
                const float4 c01 = lds128f(pbase + v * 32), c23 = lds128f(pbase + v * 32 + 16);
                const float cf[8] = {c01.x, c01.y, c01.z, c01.w, c23.x, c23.y, c23.z, c23.w};
                mbar_wait(full0 + 8 * v, 0, it);
                if (kind == 0 || warp < 5) {
                    uint32_t w[12];
#pragma unroll
                    for (int e = 0; e < 12; e++) w[e] = lds32(wordoff + v * TILE + e * 128);
#pragma unroll
                    for (int e = 0; e < 12; e++) {
                        const int r = e / 3, k = e - r * 3;
                        const float lo = bf_lo(w[e]), hi = bf_hi(w[e]);
                        acc[4 * k]     = fmaf(lo, cf[2 * r], acc[4 * k]);
                        acc[4 * k + 1] = fmaf(lo, cf[2 * r + 1], acc[4 * k + 1]);
                        acc[4 * k + 2] = fmaf(hi, cf[2 * r], acc[4 * k + 2]);
                        acc[4 * k + 3] = fmaf(hi, cf[2 * r + 1], acc[4 * k + 3]);
                    }
                }
                __syncwarp();
                if (lane == 0) mbar_arrive(empty0 + 8 * v);
            }
            if (kind == 0 && tid == 0) STAMP(11);
            float4* red = reinterpret_cast<float4*>(smem + SM_RED) + kind * (8 * 96);
#pragma unroll
            for (int k = 0; k < 3; k++)
                red[warp * 96 + lane + 32 * k] = make_float4(acc[4 * k], acc[4 * k + 1], acc[4 * k + 2], acc[4 * k + 3]);
            bar_sync(2, 256);
            const int u = tid - kind * 96;
            if (u >= 0 && u < 96) {
                float4 s = red[u];
#pragma unroll
                for (int w = 1; w < 8; w++) {
                    const float4 t = red[w * 96 + u];
                    s.x += t.x; s.y += t.y; s.z += t.z; s.w += t.w;
                }
                st_tag4((kind ? g_h : g_q) + c * 96 + u, s, tag);
            }
            __syncwarp();
        }
        if (tid == 0) STAMP(2);
        if (tid < 96) {
            const float4* q = g_q + h * 4 * 96 + tid;
            uint4 v0 = make_uint4(0, 0, 0, 0), v1 = v0, v2 = v0, v3 = v0;
#pragma unroll 1
            while (true) {
                reload4(v0, q, bad4(v0, tag)); reload4(v1, q + 96, bad4(v1, tag));
                reload4(v2, q + 192, bad4(v2, tag)); reload4(v3, q + 288, bad4(v3, tag));
                if (!(bad4(v0, tag) | bad4(v1, tag) | bad4(v2, tag) | bad4(v3, tag)) || ++it >= SPIN_LIMIT) break;
                if (QPOLL_NS) __nanosleep(QPOLL_NS);
            }
            const float4 a = asf4(v0), b4 = asf4(v1), cc = asf4(v2), d = asf4(v3);
            float2* qs = reinterpret_cast<float2*>(smem + SM_Q);
            qs[tid] = make_float2(rbf((a.x + b4.x) + (cc.x + d.x)), rbf((a.z + b4.z) + (cc.z + d.z)));
            qs[96 + tid] = make_float2(rbf((a.y + b4.y) + (cc.y + d.y)), rbf((a.w + b4.w) + (cc.w + d.w)));
        }
        __syncwarp();
        bar_sync(3, 256);
        if (tid == 0) { mbar_arrive(go_q); STAMP(3); }
        const uint32_t rowoff = sb + SM_RING + (warp * 4 + g) * 384 + jj * 16;
        float sc[4];
#pragma unroll
        for (int b = 0; b < 2; b++) {
            float q[24];
#pragma unroll
            for (int k = 0; k < 3; k++) {
                const uint32_t a = sb + SM_Q + (b * 192 + (jj + 8 * k) * 8) * 4;
                const float4 lo = lds128f(a), hi = lds128f(a + 16);
                q[8 * k] = lo.x; q[8 * k + 1] = lo.y; q[8 * k + 2] = lo.z; q[8 * k + 3] = lo.w;
                q[8 * k + 4] = hi.x; q[8 * k + 5] = hi.y; q[8 * k + 6] = hi.z; q[8 * k + 7] = hi.w;
            }
            float k0 = 0.f, k1 = 0.f;
#pragma unroll 1
            for (int t = 0; t < 16; t++) {
                const int v = V_K + b * 16 + t, slot = v & (NS - 1);
                mbar_wait(full0 + 8 * slot, (v / NS) & 1, it);
                const uint32_t a = rowoff + slot * TILE;
                const uint4 u0 = lds128(a), u1 = lds128(a + 128), u2 = lds128(a + 256);
                const uint32_t uw[12] = {u0.x, u0.y, u0.z, u0.w, u1.x, u1.y, u1.z, u1.w, u2.x, u2.y, u2.z, u2.w};
                float d0 = 0.f, d1 = 0.f, d2 = 0.f, d3 = 0.f;
#pragma unroll
                for (int e = 0; e < 12; e += 2) {
                    d0 = fmaf(bf_lo(uw[e]), q[2 * e], d0);
                    d1 = fmaf(bf_hi(uw[e]), q[2 * e + 1], d1);
                    d2 = fmaf(bf_lo(uw[e + 1]), q[2 * e + 2], d2);
                    d3 = fmaf(bf_hi(uw[e + 1]), q[2 * e + 3], d3);
                }
                float d = (d0 + d1) + (d2 + d3);
                d += __shfl_xor_sync(~0u, d, 1);
                if (lane == 0) mbar_arrive(empty0 + 8 * slot);
                d += __shfl_xor_sync(~0u, d, 2);
                d += __shfl_xor_sync(~0u, d, 4);
                k0 = t == jj ? d : k0;
                k1 = t == jj + 8 ? d : k1;
            }
            sc[2 * b] = rbf(rbf(k0) * 0.07216878364870322f);
            sc[2 * b + 1] = rbf(rbf(k1) * 0.07216878364870322f);
        }
        if (tid == 0) { mbar_arrive(go_mid); STAMP(4); }
        float mx0 = fmaxf(sc[0], sc[1]), mx1 = fmaxf(sc[2], sc[3]);
#pragma unroll
        for (int o = 16; o; o >>= 1) {
            mx0 = fmaxf(mx0, __shfl_xor_sync(~0u, mx0, o));
            mx1 = fmaxf(mx1, __shfl_xor_sync(~0u, mx1, o));
        }
        if (lane == 0) { s_mx[warp] = mx0; s_mx[8 + warp] = mx1; }
        __syncwarp();
        bar_sync(4, 256);
        {
            const float4 u = lds128f(sb + SM_MX), v = lds128f(sb + SM_MX + 16);
            const float4 w = lds128f(sb + SM_MX + 32), z = lds128f(sb + SM_MX + 48);
            mx0 = fmaxf(fmaxf(fmaxf(u.x, u.y), fmaxf(u.z, u.w)), fmaxf(fmaxf(v.x, v.y), fmaxf(v.z, v.w)));
            mx1 = fmaxf(fmaxf(fmaxf(w.x, w.y), fmaxf(w.z, w.w)), fmaxf(fmaxf(z.x, z.y), fmaxf(z.z, z.w)));
            sc[0] = __expf(sc[0] - mx0); sc[1] = __expf(sc[1] - mx0);
            sc[2] = __expf(sc[2] - mx1); sc[3] = __expf(sc[3] - mx1);
            float* pt = reinterpret_cast<float*>(smem + SM_P + warp * 512) + jj * 4 + g;
            pt[0] = sc[0]; pt[32] = sc[1]; pt[64] = sc[2]; pt[96] = sc[3];
            float l0 = sc[0] + sc[1], l1 = sc[2] + sc[3];
#pragma unroll
            for (int o = 16; o; o >>= 1) {
                l0 += __shfl_xor_sync(~0u, l0, o);
                l1 += __shfl_xor_sync(~0u, l1, o);
            }
            if (lane == 0) { s_mx[16 + warp] = l0; s_mx[24 + warp] = l1; }
            __syncwarp();
        }
#pragma unroll
        for (int b = 0; b < 2; b++) {
            float acc[6];
#pragma unroll
            for (int e = 0; e < 6; e++) acc[e] = 0.f;
#pragma unroll 1
            for (int t = 0; t < 16; t++) {
                const float4 pp = lds128f(pbase + (b * 16 + t) * 16);
                const float cf[4] = {pp.x, pp.y, pp.z, pp.w};
                const int v = V_V + b * 16 + t, slot = v & (NS - 1);
                mbar_wait(full0 + 8 * slot, (v / NS) & 1, it);
                uint32_t w[12];
#pragma unroll
                for (int e = 0; e < 12; e++) w[e] = lds32(wordoff + slot * TILE + e * 128);
#pragma unroll
                for (int e = 0; e < 12; e++) {
                    const int r = e / 3, k = e - r * 3;
                    acc[2 * k] = fmaf(bf_lo(w[e]), cf[r], acc[2 * k]);
                    acc[2 * k + 1] = fmaf(bf_hi(w[e]), cf[r], acc[2 * k + 1]);
                }
                __syncwarp();
                if (lane == 0) mbar_arrive(empty0 + 8 * slot);
            }
            if (b == 1 && tid == 0) { mbar_arrive(go_end); STAMP(5); }
            float2* red2 = reinterpret_cast<float2*>(smem + SM_RED) + b * (8 * 96);
#pragma unroll
            for (int k = 0; k < 3; k++) red2[warp * 96 + lane + 32 * k] = make_float2(acc[2 * k], acc[2 * k + 1]);
            if (b == 1) mbar_wait(bar_hh, 0, it);
            bar_sync(2, 256);
            if (tid < 48) {
                const float4* red = reinterpret_cast<const float4*>(red2) + tid;
                float4 s = red[0];
#pragma unroll
                for (int w = 1; w < 8; w++) {
                    const float4 t = red[w * 48];
                    s.x += t.x; s.y += t.y; s.z += t.z; s.w += t.w;
                }
                st_tag4(reinterpret_cast<float4*>(&g_o[(b * NCTA + c) * XS]) + tid, s, tag);
            } else if (b == 0 && tid >= 64 && tid < 68) {
                const int sb_ = (tid >> 1) & 1;
                const float4 u = lds128f(sb + SM_MX + 64 + sb_ * 32), v = lds128f(sb + SM_MX + 80 + sb_ * 32);
                const float l = ((u.x + u.y) + (u.z + u.w)) + ((v.x + v.y) + (v.z + v.w)), m = sb_ ? mx1 : mx0;
                st_tag4(reinterpret_cast<float4*>(&g_o[(sb_ * NCTA + c) * XS + 192]) + (tid & 1), make_float4(m, l, m, l), tag);
            }
            if (b == 0 && tid == 0) mbar_arrive(go_st);
            __syncwarp();
        }
        if (tid == 0) STAMP(6);
    }

    const int lr = lane & 7, mi = lane >> 3;
    const uint32_t cob = sb + SM_CO + (lane >> 2) * 128 + (lane & 3) * 4;
    float4 d[4];
    uint32_t a[6][8];
#pragma unroll
    for (int m = 0; m < 4; m++) d[m] = make_float4(0.f, 0.f, 0.f, 0.f);
    mbar_wait(bar_hh, 0, it);
#pragma unroll
    for (int t = 0; t < 2; t++) {
        const int v = V_W2 + t, slot = v & (NS - 1);
        const uint32_t b = lane < 8 ? lds32(cob + t * 16) : 0u;
        mbar_wait(full0 + 8 * slot, (v / NS) & 1, it);
        load_wfrag(a[t], wfrag_addr(sb + SM_RING + slot * TILE + WLINE(warp, (lr < 6 ? lr : lr - 6), 6) * 128, mi));
        mma_w(d, a[t], b);
    }
    const int pk = c * 320 + warp * 32 + (lane >> 2);
    if ((lane & 3) == 0) {
#pragma unroll
        for (int m = 0; m < 4; m++) st_pkt(&g_fp[pk + m * 8], d[m], tag);
    }
#pragma unroll
    for (int m = 0; m < 4; m++) d[m] = make_float4(0.f, 0.f, 0.f, 0.f);
    __syncwarp();
    constexpr int VL = V_WO + 5, SL = VL & (NS - 1), PL = (VL / NS) & 1;
    const uint32_t wa = wfrag_addr(sb + SM_RING + WLINE(warp, lr, 8) * 128, mi);
    uint32_t wal = wa + SL * TILE, fin = sb + SM_FIN + ((lane >> 3) * 4 + (lane & 3)) * 32 + warp * 4;
    const float4* pub = g_sp + pk;
    const float4* ps = g_sp + (tid >> 2) * 320 + 4 * c + (tid & 3);
    uint32_t role = (c < 80 && warp < 8 ? 1u : 0u) | ((lane & 3) == 0 ? 2u : 0u) | ((lane & 4) == 0 ? 4u : 0u);
    pin(wal); pin(fin); pin(pub); pin(ps); pin(role);
#pragma unroll
    for (int t = 0; t < 5; t++) {
        const int v = V_WO + t, slot = v & (NS - 1);
        mbar_wait(full0 + 8 * slot, (v / NS) & 1, it);
        load_wfrag(a[t], wa + slot * TILE);
    }
    const bool early = __all_sync(~0u, mbar_test(full0 + 8 * SL, PL));
    if (early) load_wfrag(a[5], wal);
    mbar_wait(bar_oc, 0, it);
    uint32_t b[6];
#pragma unroll
    for (int t = 0; t < 6; t++) b[t] = lane < 8 ? lds32(cob + 32 + t * 16) : 0u;
#pragma unroll
    for (int t = 0; t < 5; t++) mma_w(d, a[t], b[t]);
    if (!early) {
        mbar_wait(full0 + 8 * SL, PL, it);
        load_wfrag(a[5], wal);
    }
    mma_w(d, a[5], b[5]);
    if (role & 2) {
#pragma unroll
        for (int m = 0; m < 4; m++) st_pkt(pub + m * 8, d[m], tag);
    }
    __syncwarp();
    if (tid == 0) STAMP(8);
    if (role & 1) {
        uint4 s0 = make_uint4(0, 0, 0, 0), s1 = s0;
#pragma unroll 1
        do {
            ld_pkt(s0, ps, bad_pkt(s0, tag));
            ld_pkt(s1, ps + 64 * 320, bad_pkt(s1, tag));
        } while (__any_sync(~0u, bad_pkt(s0, tag) | bad_pkt(s1, tag)) && ++it < SPIN_LIMIT);
        if (tid == 0) STAMP(13);
        const float4 u = asf4(s0), w = asf4(s1);
        const float r = fin_reduce(make_float4(u.x + w.x, u.y + w.y, u.z + w.z, u.w + w.w), lane);
        if (role & 4) asm volatile("st.shared.f32 [%0], %1;" ::"r"(fin), "f"(r) : "memory");
        __syncwarp();
        bar_arrive(9, 288);
    }
    PROF_END;
}

#define PROMO_O CU_TENSOR_MAP_L2_PROMOTION_L2_128B
#define PROMO_Q CU_TENSOR_MAP_L2_PROMOTION_L2_128B
typedef CUresult (*EncodeFn)(CUtensorMap*, CUtensorMapDataType, cuuint32_t, void*, const cuuint64_t*, const cuuint64_t*,
                             const cuuint32_t*, const cuuint32_t*, CUtensorMapInterleave, CUtensorMapSwizzle,
                             CUtensorMapL2promotion, CUtensorMapFloatOOBfill);

void encode_2d(EncodeFn fn, CUtensorMap* map, void* ptr, int cols, int rows, int box_rows) {
    const cuuint64_t dims[2] = {(cuuint64_t)cols, (cuuint64_t)rows}, strides[1] = {(cuuint64_t)cols * 2};
    const cuuint32_t box[2] = {(cuuint32_t)DH, (cuuint32_t)box_rows}, es[2] = {1, 1};
    fn(map, CU_TENSOR_MAP_DATA_TYPE_BFLOAT16, 2, ptr, dims, strides, box, es, CU_TENSOR_MAP_INTERLEAVE_NONE,
       CU_TENSOR_MAP_SWIZZLE_NONE, PROMO_Q, CU_TENSOR_MAP_FLOAT_OOB_FILL_NONE);
}

void encode_3d(EncodeFn fn, CUtensorMap* map, void* ptr, int rows, int box_rows) {
    const cuuint64_t dims[3] = {64, (cuuint64_t)rows, 10}, strides[2] = {(cuuint64_t)D * 2, 128};
    const cuuint32_t box[3] = {64, (cuuint32_t)box_rows, 10}, es[3] = {1, 1, 1};
    const int rank = 3;
    CUresult r = fn(map, CU_TENSOR_MAP_DATA_TYPE_BFLOAT16, rank, ptr, dims, strides, box, es, CU_TENSOR_MAP_INTERLEAVE_NONE,
       CU_TENSOR_MAP_SWIZZLE_128B, PROMO_O, CU_TENSOR_MAP_FLOAT_OOB_FILL_NONE);
    (void)r;
}

}

#define PACE_T0 0
static double pace_gbs = PACE_GBS, pace_t0 = PACE_T0;
extern "C" void kernel_launch(void* const* d_in, const int* in_sizes, int n_in, void* d_out, int out_size) {
    (void)in_sizes; (void)n_in; (void)out_size;
    static EncodeFn encode = nullptr;
    if (!encode) {
        void* fn = nullptr;
        cudaDriverEntryPointQueryResult qr;
        cudaGetDriverEntryPoint("cuTensorMapEncodeTiled", &fn, cudaEnableDefault, &qr);
        encode = (EncodeFn)fn;
        cudaFuncSetAttribute(fused_decode_kernel, cudaFuncAttributeMaxDynamicSharedMemorySize, SM_TOTAL);
    }
    CUtensorMap map_wq, map_w1, map_w2, map_wo;
    encode_2d(encode, &map_wq, d_in[3], QD, D, 32);
    encode_2d(encode, &map_w1, d_in[6], FF, D, 20);
    encode_3d(encode, &map_w2, d_in[8], FF, 6);
    encode_3d(encode, &map_wo, d_in[4], QD, 8);
    Params p;
    p.x  = (const __nv_bfloat16*)d_in[0];
    p.k  = (const __nv_bfloat16*)d_in[1];
    p.v  = (const __nv_bfloat16*)d_in[2];
    p.b1 = (const __nv_bfloat16*)d_in[7];
    p.b2 = (const __nv_bfloat16*)d_in[9];
    p.out = (__nv_bfloat16*)d_out;
    p.w2 = (const __nv_bfloat16*)d_in[8];
    p.wo = (const __nv_bfloat16*)d_in[4];
    p.tstart = (uint32_t)pace_t0;
    p.pace = (uint32_t)(256.0 * NCTA / pace_gbs * 65536.0);
    fused_decode_kernel<<<NCTA, NTHR, SM_TOTAL, cudaStreamPerThread>>>(map_wq, map_w1, map_w2, map_wo, p);
}
```

```cpp
#include <cuda.h>
#include <cuda_runtime.h>
#include <cuda_bf16.h>
#include <stdint.h>

namespace {

constexpr int D = 640, DH = 192, SK = 8192, WIN = 2048, FF = 1536, QD = 6144;
constexpr int NCTA = 128, NTHR = 512;
constexpr int TILE = 12288;
constexpr int NS = 16;
constexpr int V_WQ = 0, V_W1 = 5, V_K = 7, V_WO = 71, V_WS = 76, NT = 78, NW2 = 6;
constexpr int WT = 20 * 384;
constexpr int OT = 8 * D * 2;
constexpr int NPRE = 2;
constexpr int W2_EARLY = 2;
constexpr double PACE_OF_PEAK = 0.968;
constexpr int BURST = 5 * TILE / 4;
constexpr int DEPTH = 7, DEPTH_TAIL = 8;
constexpr int BACK = 4, BACK_FROM = 26;
constexpr uint32_t STEP1 = 50, STEP2 = 200;
constexpr int LATE = 28;
constexpr uint32_t LATE_NS = 400, EARLY_NS = 2000;
constexpr int OROW = 56;
constexpr unsigned SPIN_LIMIT = 1u << 20;

constexpr int SM_RING = 0;
constexpr int SM_RED  = SM_RING + NS * TILE;
constexpr int SM_Q    = SM_RED + 8 * 384 * 4;
constexpr int SM_P    = SM_Q + 8 * 384 * 4;
constexpr int SM_CO   = SM_P + 8 * 256;
constexpr int SM_FIN  = SM_CO + 48 * 8;
constexpr int SM_HH   = SM_RED + 4096;
constexpr int SM_GP   = SM_FIN + 256 * 4;
constexpr int SM_SH   = SM_GP + 128 * 4;
constexpr int SM_BAR  = SM_SH + 16;
constexpr int SM_TOTAL = SM_BAR + (2 * NS + 16 + 10 + NW2) * 8;

__device__ float4 g_q[NCTA * 96];
__device__ float4 g_h[NCTA * 96];
__device__ float  g_o[64 * 4 * 64 * OROW];
__device__ float4 g_hh[FF / 2];
__device__ float4 g_sp[NCTA * 320];
__device__ unsigned g_shift[4 * 32];
__device__ unsigned g_epoch;

struct Params {
    const __nv_bfloat16 *x, *k, *v, *b1, *b2, *wo;
    __nv_bfloat16* out;
    uint32_t pace;
};

__device__ __forceinline__ void mbar_init(uint32_t a, int cnt) {
    asm volatile("mbarrier.init.shared::cta.b64 [%0], %1;" ::"r"(a), "r"(cnt) : "memory");
}
__device__ __forceinline__ void mbar_expect(uint32_t a, uint32_t bytes) {
    asm volatile("mbarrier.arrive.expect_tx.shared::cta.b64 _, [%0], %1;" ::"r"(a), "r"(bytes) : "memory");
}
__device__ __forceinline__ void mbar_arrive(uint32_t a) {
    asm volatile("mbarrier.arrive.shared::cta.b64 _, [%0];" ::"r"(a) : "memory");
}
__device__ __forceinline__ void mbar_arrive_n(uint32_t a, uint32_t n) {
    asm volatile("mbarrier.arrive.shared::cta.b64 _, [%0], %1;" ::"r"(a), "r"(n) : "memory");
}
__device__ __forceinline__ void mbar_wait(uint32_t a, uint32_t parity, unsigned& n) {
    asm volatile(
        "{\n.reg .pred p, q;\n"
        "W_%=:\n"
        ".pragma \"nounroll\";\n"
        "mbarrier.try_wait.parity.shared::cta.b64 p, [%1], %2;\n"
        "@!p add.u32 %0, %0, 1;\n"
        "setp.lt.and.u32 q, %0, %3, !p;\n"
        "@q bra W_%=;\n}"
        : "+r"(n) : "r"(a), "r"(parity), "n"(SPIN_LIMIT) : "memory");
}
__device__ __forceinline__ uint32_t gtime32() {
    uint32_t t;
    asm volatile("mov.u32 %0, %%globaltimer_lo;" : "=r"(t) :: "memory");
    return t;
}
__host__ __device__ constexpr int vof(int i) { return i < NPRE ? V_K + i : i < V_K + NPRE ? i - NPRE : i; }
__host__ __device__ constexpr int tile_bytes(int v) { return (v < V_W1 || (v >= V_K && v < V_WO)) ? TILE : v < V_K ? WT : v < V_WS ? OT : OT / 2; }
__host__ __device__ constexpr int issued_before(int i) {
    return i <= NPRE + 5 ? i * TILE : i <= NPRE + 7 ? (NPRE + 5) * TILE + (i - NPRE - 5) * WT : i <= V_WO ? 2 * WT + (i - 2) * TILE
         : i <= V_WS ? 2 * WT + (V_WO - 2) * TILE + (i - V_WO) * OT : 2 * WT + (V_WO - 2) * TILE + 5 * OT + (i - V_WS) * (OT / 2);
}
__host__ __device__ constexpr int sched_pos(int i) { return (issued_before(i) - BURST) / 256; }
__device__ __forceinline__ void mbar_sleep(uint32_t a, unsigned& n) {
    asm volatile(
        "{\n.reg .pred p;\n"
        "W_%=:\n"
        ".pragma \"nounroll\";\n"
        "mbarrier.try_wait.parity.shared::cta.b64 p, [%1], 0, %3;\n"
        "@p bra D_%=;\n"
        "add.u32 %0, %0, 2048;\n"
        "setp.lt.u32 p, %0, %2;\n"
        "@p bra W_%=;\n"
        "D_%=:\n}"
        : "+r"(n) : "r"(a), "n"(SPIN_LIMIT), "r"(100000) : "memory");
}
__device__ __forceinline__ bool elect_one() {
    uint32_t r;
    asm volatile("{\n.reg .pred p;\nelect.sync _|p, 0xffffffff;\nselp.u32 %0, 1, 0, p;\n}" : "=r"(r));
    return r;
}
__device__ __forceinline__ void bulk_load(uint32_t dst, const void* src, uint32_t bytes, uint32_t mbar, uint64_t pol) {
    asm volatile("cp.async.bulk.shared::cluster.global.mbarrier::complete_tx::bytes.L2::cache_hint [%0], [%1], %2, [%3], %4;"
                 ::"r"(dst), "l"(src), "r"(bytes), "r"(mbar), "l"(pol) : "memory");
}
__device__ __forceinline__ void box_load(uint32_t dst, const CUtensorMap* map, int col, int row, uint32_t mbar, uint64_t pol) {
    asm volatile("cp.async.bulk.tensor.2d.shared::cluster.global.mbarrier::complete_tx::bytes.L2::cache_hint [%0], [%1, {%2, %3}], [%4], %5;"
                 ::"r"(dst), "l"(map), "r"(col), "r"(row), "r"(mbar), "l"(pol) : "memory");
}
__device__ __forceinline__ void box3_load(uint32_t dst, const CUtensorMap* map, int row, uint32_t mbar, uint64_t pol) {
    asm volatile("cp.async.bulk.tensor.3d.shared::cluster.global.mbarrier::complete_tx::bytes.L2::cache_hint [%0], [%1, {0, %2, 0}], [%3], %4;"
                 ::"r"(dst), "l"(map), "r"(row), "r"(mbar), "l"(pol) : "memory");
}
__device__ __forceinline__ bool mbar_test(uint32_t a, uint32_t parity) {
    uint32_t ok;
    asm volatile("{\n.reg .pred p;\nmbarrier.test_wait.parity.shared::cta.b64 p, [%1], %2;\nselp.u32 %0, 1, 0, p;\n}"
                 : "=r"(ok) : "r"(a), "r"(parity) : "memory");
    return ok;
}
__device__ __forceinline__ void ldsm4(uint32_t (&a)[4], uint32_t addr) {
    asm volatile("ldmatrix.sync.aligned.m8n8.x4.shared.b16 {%0,%1,%2,%3}, [%4];"
                 : "=r"(a[0]), "=r"(a[1]), "=r"(a[2]), "=r"(a[3]) : "r"(addr) : "memory");
}
__device__ __forceinline__ void ldsm4t(uint32_t (&a)[4], uint32_t addr) {
    asm volatile("ldmatrix.sync.aligned.m8n8.x4.trans.shared.b16 {%0,%1,%2,%3}, [%4];"
                 : "=r"(a[0]), "=r"(a[1]), "=r"(a[2]), "=r"(a[3]) : "r"(addr) : "memory");
}
__device__ __forceinline__ void mma16(float4& d, const uint32_t (&a)[4], uint32_t b0, uint32_t b1) {
    asm("mma.sync.aligned.m16n8k16.row.col.f32.bf16.bf16.f32 {%0,%1,%2,%3}, {%4,%5,%6,%7}, {%8,%9}, {%0,%1,%2,%3};"
        : "+f"(d.x), "+f"(d.y), "+f"(d.z), "+f"(d.w) : "r"(a[0]), "r"(a[1]), "r"(a[2]), "r"(a[3]), "r"(b0), "r"(b1));
}
__device__ __forceinline__ void mma8(float4& d, uint32_t a0, uint32_t a1, uint32_t b) {
    asm("mma.sync.aligned.m16n8k8.row.col.f32.bf16.bf16.f32 {%0,%1,%2,%3}, {%4,%5}, {%6}, {%0,%1,%2,%3};"
        : "+f"(d.x), "+f"(d.y), "+f"(d.z), "+f"(d.w) : "r"(a0), "r"(a1), "r"(b));
}
__device__ __forceinline__ void bar_sync(int id, int cnt) { asm volatile("bar.sync %0, %1;" ::"r"(id), "r"(cnt) : "memory"); }
__device__ __forceinline__ void bar_arrive(int id, int cnt) { asm volatile("bar.arrive %0, %1;" ::"r"(id), "r"(cnt) : "memory"); }

__device__ __forceinline__ uint4 lds128(uint32_t a) {
    uint4 v;
    asm volatile("ld.shared.v4.u32 {%0,%1,%2,%3}, [%4];" : "=r"(v.x), "=r"(v.y), "=r"(v.z), "=r"(v.w) : "r"(a) : "memory");
    return v;
}
__device__ __forceinline__ float4 lds128f(uint32_t a) {
    float4 v;
    asm volatile("ld.shared.v4.f32 {%0,%1,%2,%3}, [%4];" : "=f"(v.x), "=f"(v.y), "=f"(v.z), "=f"(v.w) : "r"(a) : "memory");
    return v;
}
__device__ __forceinline__ uint32_t lds32(uint32_t a) {
    uint32_t v;
    asm volatile("ld.shared.u32 %0, [%1];" : "=r"(v) : "r"(a) : "memory");
    return v;
}
__device__ __forceinline__ uint32_t tagw(float v, uint32_t tag) { return (__float_as_uint(v) & ~3u) | tag; }
__device__ __forceinline__ void st_tag4(float4* p, float4 v, uint32_t tag) {
    asm volatile("st.relaxed.gpu.global.v4.u32 [%0], {%1,%2,%3,%4};"
                 ::"l"(p), "r"(tagw(v.x, tag)), "r"(tagw(v.y, tag)), "r"(tagw(v.z, tag)), "r"(tagw(v.w, tag)) : "memory");
}
__device__ __forceinline__ void st_64(void* p, uint32_t a, uint32_t b) {
    asm volatile("{\n.reg .b64 x;\nmov.b64 x, {%1, %2};\nst.relaxed.gpu.global.b64 [%0], x;\n}" ::"l"(p), "r"(a), "r"(b) : "memory");
}
__device__ __forceinline__ void st_zero4(void* p) {
    asm volatile("st.relaxed.gpu.global.v4.u32 [%0], {%1,%1,%1,%1};" ::"l"(p), "r"(0) : "memory");
}
__device__ __forceinline__ uint32_t next_tag() {
    uint32_t e;
    asm volatile("ld.relaxed.gpu.global.u32 %0, [%1];" : "=r"(e) : "l"(&g_epoch) : "memory");
    return e == 3 ? 1 : e + 1;
}
__device__ __forceinline__ uint32_t ld_x1(const float* p) {
    uint32_t v;
    asm volatile("ld.relaxed.gpu.global.u32 %0, [%1];" : "=r"(v) : "l"(p) : "memory");
    return v;
}
__device__ __forceinline__ uint2 take2(const void* p, bool want) {
    uint2 t;
    asm volatile("{\n.reg .pred q;\n.reg .b64 x;\nsetp.ne.u32 q, %3, 0;\nmov.b64 x, 0;\n"
                 "@q atom.relaxed.gpu.global.exch.b64 x, [%2], x;\nmov.b64 {%0, %1}, x;\n}"
                 : "=r"(t.x), "=r"(t.y) : "l"(p), "r"((uint32_t)want) : "memory");
    return t;
}
__device__ __forceinline__ void ld_2x64(uint4& v, const float4* p, bool want) {
    asm volatile("{\n.reg .pred q;\n.reg .b64 lo, hi;\nsetp.ne.u32 q, %5, 0;\nmov.b64 lo, {%0, %1};\nmov.b64 hi, {%2, %3};\n"
                 "@q ld.relaxed.gpu.global.v2.b64 {lo, hi}, [%4];\nmov.b64 {%0, %1}, lo;\nmov.b64 {%2, %3}, hi;\n}"
                 : "+r"(v.x), "+r"(v.y), "+r"(v.z), "+r"(v.w) : "l"(p), "r"((uint32_t)want) : "memory");
}
__device__ __forceinline__ uint32_t bad_2x64(const uint4& v, uint32_t tag) { return ((v.x ^ tag) | (v.z ^ tag)) & 3u; }
__device__ __forceinline__ void st_pkt(const float4* p, float4 v, uint32_t tag) {
    asm volatile("{\n.reg .b128 x;\n.reg .b64 lo, hi;\nmov.b64 lo, {%1, %2};\nmov.b64 hi, {%3, %4};\nmov.b128 x, {lo, hi};\n"
                 "st.relaxed.gpu.global.b128 [%0], x;\n}"
                 ::"l"(p), "r"(tagw(v.x, tag)), "r"(__float_as_uint(v.y)), "r"(__float_as_uint(v.z)), "r"(__float_as_uint(v.w)) : "memory");
}
__device__ __forceinline__ void ld_pkt(uint4& v, const float4* p, bool want) {
    asm volatile("{\n.reg .pred q;\n.reg .b128 x;\n.reg .b64 lo, hi;\nsetp.ne.u32 q, %5, 0;\n"
                 "mov.b64 lo, {%0, %1};\nmov.b64 hi, {%2, %3};\nmov.b128 x, {lo, hi};\n"
                 "@q ld.relaxed.gpu.global.b128 x, [%4];\n"
                 "mov.b128 {lo, hi}, x;\nmov.b64 {%0, %1}, lo;\nmov.b64 {%2, %3}, hi;\n}"
                 : "+r"(v.x), "+r"(v.y), "+r"(v.z), "+r"(v.w) : "l"(p), "r"((uint32_t)want) : "memory");
}
__device__ __forceinline__ bool bad_pkt(const uint4& v, uint32_t tag) { return (v.x & 3u) != tag; }
template <class T> __device__ __forceinline__ void pin(T*& p) { asm volatile("" : "+l"(p)); }
__device__ __forceinline__ void pin(uint32_t& v) { asm volatile("" : "+r"(v)); }
__device__ __forceinline__ float untag(uint32_t w) { return __uint_as_float(w & ~3u); }
__device__ __forceinline__ float4 pkt_val(const uint4& v) {
    return make_float4(untag(v.x), __uint_as_float(v.y), __uint_as_float(v.z), __uint_as_float(v.w));
}
__device__ __forceinline__ float4 val_2x64(const uint4& v) {
    return make_float4(untag(v.x), __uint_as_float(v.y), untag(v.z), __uint_as_float(v.w));
}
__device__ __forceinline__ float bf_lo(uint32_t w) { return __uint_as_float(w << 16); }
__device__ __forceinline__ float bf_hi(uint32_t w) { return __uint_as_float(w & 0xffff0000u); }
__device__ __forceinline__ float rbf(float v) { return __bfloat162float(__float2bfloat16_rn(v)); }

__global__ void __launch_bounds__(NTHR, 1)
fused_decode_kernel(const __grid_constant__ CUtensorMap map_wq, const __grid_constant__ CUtensorMap map_w1,
                    const __grid_constant__ CUtensorMap map_k, const __grid_constant__ CUtensorMap map_v,
                    const __grid_constant__ CUtensorMap map_wo, const __grid_constant__ CUtensorMap map_w2, const Params p) {
    extern __shared__ __align__(1024) unsigned char smem[];
    const uint32_t sb = (uint32_t)__cvta_generic_to_shared(smem);
    const int hw = threadIdx.x >> 5, lane = threadIdx.x & 31;
    const int warp = hw == 0 ? 10 : hw <= 10 ? hw - 1 : hw, tid = warp * 32 + lane;
    const int c = blockIdx.x, h = c >> 2, j = c & 3;
    const int grp = c >> 6, mem = c & 63;
    const uint32_t full0 = sb + SM_BAR, empty0 = full0 + NS * 8, qbar0 = empty0 + NS * 8;
    const uint32_t bar_ph = qbar0 + 16 * 8, bar_oc = bar_ph + 8, go_q = bar_ph + 16, go_end = bar_ph + 24;
    const uint32_t go_o = bar_ph + 32, go_v = bar_ph + 48, bar_wt = bar_ph + 64, bar_w2 = bar_ph + 80;
    float* s_co = reinterpret_cast<float*>(smem + SM_CO);
    unsigned it = 0;

    uint64_t pol;
    asm volatile("createpolicy.fractional.L2::evict_first.b64 %0, 1.0;" : "=l"(pol));
    const int fi = grp * 48 + mem, fc = mem < 48 && fi % 12 < 5 ? fi / 12 * 5 + fi % 12 : 40;
    const bool latec = (h & 15) * 2 >= LATE;
    const int own2 = (h & 15) * 2;
    const int line0 = (grp * 16 * SK + (SK - WIN) + mem * 32) * 3;
    auto kv_line = [&](int u) { return line0 + ((u >> 2) + (u & 2) * 16) * (SK * 3); };
    uint32_t t0 = 0;
    if (threadIdx.x < 32) {
        if (elect_one()) {
#pragma unroll
            for (int i = 0; i < NPRE; i++) {
                const int v = V_K + i;
                mbar_init(full0 + 8 * v, 1);
                mbar_expect(full0 + 8 * v, TILE);
                bulk_load(sb + SM_RING + v * TILE, reinterpret_cast<const char*>(i ? p.v : p.k) + (size_t)line0 * 128, TILE, full0 + 8 * v, pol);
            }
        }
        t0 = gtime32();
        __syncwarp();
    }
    if (threadIdx.x < 32) {
        const bool leader = elect_one();
        if (leader) {
            asm volatile("prefetch.tensormap [%0];" ::"l"(&map_wq) : "memory");
            asm volatile("prefetch.tensormap [%0];" ::"l"(&map_w1) : "memory");
#pragma unroll
            for (int s = 0; s < NS; s++) {
                if (s < V_K || s >= V_K + NPRE) mbar_init(full0 + 8 * s, 1);
                mbar_init(empty0 + 8 * s, 8);
            }
#pragma unroll
            for (int s = 0; s < 16; s++) mbar_init(qbar0 + 8 * s, 1);
            asm volatile("st.volatile.shared.u32 [%0], 0;" ::"r"(sb + SM_SH) : "memory");
#pragma unroll
            for (int s = 0; s < 10 + NW2; s++) mbar_init(bar_ph + 8 * s, s == 1 ? 4 : 1);
        }
        __syncwarp();
        bar_arrive(1, NTHR);
        uint32_t epoch;
        asm volatile("ld.relaxed.gpu.global.u32 %0, [%1];" : "=r"(epoch) : "l"(&g_epoch) : "memory");
        const int fb = lane >> 4, fcol = 16 * fc + 2 * (lane & 7) + ((lane >> 3) & 1);
        unsigned short xo16 = 0, b216 = 0;
        if (fc < 40) {
            asm volatile("ld.volatile.global.u16 %0, [%1];" : "=h"(xo16) : "l"(p.x + fb * D + fcol) : "memory");
            asm volatile("ld.volatile.global.u16 %0, [%1];" : "=h"(b216) : "l"(p.b2 + fcol) : "memory");
        }
        __syncwarp();
        if (leader) {
            asm volatile("prefetch.tensormap [%0];" ::"l"(&map_k) : "memory");
            asm volatile("prefetch.tensormap [%0];" ::"l"(&map_v) : "memory");
            auto gate = [&](int v, uint32_t bytes, int dv, uint32_t due) {
                const uint32_t slot8 = 8 * (v & (NS - 1));
                if (v >= NS) mbar_wait(empty0 + slot8, ((v / NS) & 1) ^ 1, it);
                mbar_expect(full0 + slot8, bytes);
                if (dv >= 0) mbar_wait(full0 + 8 * (dv & (NS - 1)), (dv / NS) & 1, it);
                while (gtime32() - t0 < due) {}
            };
            auto due_of = [&](int i) { return issued_before(i) >= BURST ? (uint32_t)(sched_pos(i) * p.pace) >> 16 : 0u; };
            constexpr int I0 = V_K + NPRE + DEPTH;
#pragma unroll
            for (int i = NPRE; i < I0; i++) {
                const int v = vof(i);
                const uint32_t fbar = full0 + 8 * (v & (NS - 1)), dst = sb + SM_RING + (v & (NS - 1)) * TILE;
                gate(v, tile_bytes(v), i >= DEPTH ? vof(i - DEPTH) : -1, due_of(i));
                if (v < V_W1) box_load(dst, &map_wq, h * DH, 160 * j + 32 * v, fbar, pol);
                else if (v < V_K) box_load(dst, &map_w1, (c & 7) * DH, 40 * (c >> 3) + 20 * (v - V_W1), fbar, pol);
                else box_load(dst, ((v - V_K) & 1) ? &map_v : &map_k, 0, kv_line(v - V_K), fbar, pol);
            }
            uint32_t duefp = sched_pos(I0) * p.pace;
            const uint32_t tg = epoch == 3 ? 1 : epoch + 1;
            unsigned* shiftp = &g_shift[tg * 32];
            if (c == 0) asm volatile("st.relaxed.gpu.global.u32 [%0], 0;" ::"l"(&g_shift[(tg == 3 ? 1 : tg + 1) * 32]) : "memory");
            uint32_t shift = 0;
#pragma unroll 1
            for (int v = I0; v < V_WO; v++) {
                const CUtensorMap* map = ((v - V_K) & 1) ? &map_v : &map_k;
                uint32_t ln = kv_line(v - V_K), fbar = full0 + 8 * (v & (NS - 1)), dst = sb + SM_RING + (v & (NS - 1)) * TILE;
                pin(map); pin(ln); pin(fbar); pin(dst);
                gate(v, TILE, v - DEPTH, duefp >> 16);
                box_load(dst, map, 0, ln, fbar, pol);
                uint32_t seen;
                asm volatile("ld.volatile.shared.u32 %0, [%1];" : "=r"(seen) : "r"(sb + SM_SH) : "memory");
                seen = max(seen, shift);
                t0 += seen - shift;
                shift = seen;
                if (v >= BACK_FROM && !mbar_test(full0 + 8 * ((v - BACK) & (NS - 1)), ((v - BACK) / NS) & 1)) {
                    const bool far = !mbar_test(full0 + 8 * ((v - BACK - 1) & (NS - 1)), ((v - BACK - 1) / NS) & 1);
                    asm volatile("red.relaxed.gpu.global.max.u32 [%0], %1;" ::"l"(shiftp), "r"(shift + (far ? STEP2 : STEP1)) : "memory");
                }
                duefp += (TILE / 256) * p.pace;
            }
            if (latec) asm volatile("prefetch.tensormap [%0];" ::"l"(&map_wo) : "memory");
            if (fc < 40) asm volatile("prefetch.tensormap [%0];" ::"l"(&map_w2) : "memory");
            auto w2_slab = [&](int i) {
                const int v = NT + i;
                mbar_wait(empty0 + 8 * (v & (NS - 1)), ((v / NS) & 1) ^ 1, it);
                mbar_expect(bar_w2 + 8 * i, 8192);
                box_load(sb + SM_RING + (v & (NS - 1)) * TILE, &map_w2, fc * 16, i * 256, bar_w2 + 8 * i, pol);
            };
#pragma unroll
            for (int v = V_WO; v < NT; v++) {
                const uint32_t fbar = full0 + 8 * (v & (NS - 1)), dst = sb + SM_RING + (v & (NS - 1)) * TILE;
                if (latec) {
                    if (v == NT - 1) break;
                    gate(v, OT, v - DEPTH_TAIL, due_of(v));
                    box3_load(dst, &map_wo, c * 48 + (v - V_WO) * 8, fbar, pol);
                    continue;
                }
                gate(v, tile_bytes(v), v - DEPTH_TAIL, due_of(v));
                bulk_load(dst, p.wo + (c * 48 + (v < V_WS ? (v - V_WO) * 8 : 40 + (v - V_WS) * 4)) * D, tile_bytes(v), fbar, pol);
                if (fc < 40 && v >= NT - 1 - W2_EARLY && v < NT - 1) w2_slab(v - (NT - 1 - W2_EARLY));
            }
            if (fc < 40) {
#pragma unroll
                for (int i = W2_EARLY; i < NW2; i++) w2_slab(i);
            }
        }
        __syncwarp();
        const uint32_t tag = epoch == 3 ? 1 : epoch + 1;
        const float xo = bf_lo(xo16), b2v = bf_lo(b216);
        if (fc < 40) {
            __nv_bfloat16* dst = p.out + fb * D + fcol;
            uint32_t fa = sb + SM_FIN + lane * 32, ga = sb + SM_GP + lane * 16;
            pin(dst); pin(fa); pin(ga);
            bar_sync(8, 160);
            const float4 gq = lds128f(ga);
            const float f = rbf(rbf((gq.x + gq.y) + (gq.z + gq.w)) + b2v);
            const float gate = rbf(__fdividef(f, 1.f + __expf(-f)));
            bar_sync(9, 288);
            const float4 u = lds128f(fa), w = lds128f(fa + 16);
            const float s = ((u.x + u.y) + (u.z + u.w)) + ((w.x + w.y) + (w.z + w.w));
            *dst = __float2bfloat16_rn(xo + rbf(rbf(s) * gate));
            if (c == 0 && lane == 0) asm volatile("st.relaxed.gpu.global.u32 [%0], %1;" ::"l"(&g_epoch), "r"(tag) : "memory");
        }
        return;
    }

    if (warp == 15) {
        const unsigned* src = &g_shift[next_tag() * 32];
        bar_sync(1, NTHR);
        if (lane == 0) {
#pragma unroll 1
            while (!mbar_test(go_end, 0) && ++it < SPIN_LIMIT) {
                uint32_t v;
                asm volatile("ld.relaxed.gpu.global.u32 %0, [%1];" : "=r"(v) : "l"(src) : "memory");
                asm volatile("st.volatile.shared.u32 [%0], %1;" ::"r"(sb + SM_SH), "r"(v) : "memory");
                __nanosleep(200);
            }
        }
        return;
    }
    uint32_t tag;
    if (warp >= 11) {
        const int fb = lane >= 12, ff = lane - fb * 12;
        float b1v = 0.f, hsq = 0.f;
        if (warp == 11) {
#pragma unroll 1
            for (int i = lane; i < 96; i += 32) { st_zero4(&g_q[c * 96 + i]); st_zero4(&g_h[c * 96 + i]); }
        } else if (warp == 12 && lane < 24) {
            b1v = __bfloat162float(p.b1[c * 12 + ff]);
        }
        tag = next_tag();
        __syncwarp();
        bar_sync(1, NTHR);
        mbar_sleep(go_q, it);
#pragma unroll 1
        for (int k = warp - 11; k < 16; k += 4) {
            const float4* src = g_q + (grp * 16 + k) * 4 * 96 + lane;
            uint4 v[12];
#pragma unroll
            for (int i = 0; i < 12; i++) v[i] = make_uint4(0, 0, 0, 0);
#pragma unroll 1
            while (true) {
#pragma unroll
                for (int i = 0; i < 12; i++) ld_pkt(v[i], src + i * 32, bad_pkt(v[i], tag));
                bool bad = false;
#pragma unroll
                for (int i = 0; i < 12; i++) bad |= bad_pkt(v[i], tag);
                if (!__any_sync(~0u, bad) || ++it >= SPIN_LIMIT) break;
                __nanosleep(200);
            }
            __nv_bfloat162* qs = reinterpret_cast<__nv_bfloat162*>(smem + SM_Q) + k * 192 + (lane & 3) * 24 + (lane >> 2);
#pragma unroll
            for (int i = 0; i < 3; i++) {
                const float4 a = pkt_val(v[i]), b = pkt_val(v[i + 3]), cc = pkt_val(v[i + 6]), d = pkt_val(v[i + 9]);
                qs[i * 8] = __floats2bfloat162_rn((a.x + b.x) + (cc.x + d.x), (a.z + b.z) + (cc.z + d.z));
                qs[96 + i * 8] = __floats2bfloat162_rn((a.y + b.y) + (cc.y + d.y), (a.w + b.w) + (cc.w + d.w));
            }
            __syncwarp();
            if (lane == 0) mbar_arrive(qbar0 + 8 * k);
        }
        if (warp == 11) {
#pragma unroll 1
            for (int i = lane; i < 320; i += 32) st_zero4(&g_sp[c * 320 + i]);
        } else if (warp == 12 && lane < 24) {
            const float* src = reinterpret_cast<const float*>(g_h + (c >> 4) * 96) + ((c & 15) * 12 + ff) * 2 + fb;
            uint32_t v[16], bad;
#pragma unroll 1
            do {
                bad = 0;
#pragma unroll
                for (int r = 0; r < 16; r++) v[r] = ld_x1(src + r * 8 * 384);
#pragma unroll
                for (int r = 0; r < 16; r++) bad |= (v[r] ^ tag) & 3u;
                if (bad) __nanosleep(200);
            } while (bad && ++it < SPIN_LIMIT);
            float s = 0.f;
#pragma unroll
            for (int r = 0; r < 16; r++) s += untag(v[r]);
            float hv = rbf(rbf(s) + b1v);
            hv = hv > 0.f ? hv : 0.f;
            hsq = rbf(hv * hv);
        }
        if (warp == 12) {
            const int u2 = lane < 6 ? 2 * lane : 0;
            const float4 pk = make_float4(__shfl_sync(~0u, hsq, u2), __shfl_sync(~0u, hsq, 12 + u2),
                                          __shfl_sync(~0u, hsq, u2 + 1), __shfl_sync(~0u, hsq, 13 + u2));
            if (lane < 6) st_pkt(&g_hh[c * 6 + lane], pk, tag);
        }
        __syncwarp();
        if (lane == 0 && warp == 11) mbar_arrive(bar_ph);
        const int b = (warp - 11) >> 1, ht = (tid - 352) & 63, p4 = ht & 15, mg = ht >> 4;
        float* part = reinterpret_cast<float*>(smem + SM_RED) + b * 256;
        const float4* row = reinterpret_cast<const float4*>(g_o + (((grp * 32 + own2 + b) * 4 + j) * 64 + mg * 16) * OROW) + p4;
        pin(row);
        const bool late = own2 + b >= LATE;
        mbar_sleep(go_v + 8 * b, it);
        { const uint32_t tw = gtime32(); while (gtime32() - tw < (late ? LATE_NS : EARLY_NS)) { if (!late) __nanosleep(200); } }
        uint4 v[16];
#pragma unroll
        for (int k = 0; k < 16; k++) {
            v[k] = make_uint4(tag, tag, tag, tag);
            ld_2x64(v[k], row + k * (OROW / 4), p4 < 12);
        }
        mbar_wait(bar_wt + 8 * b, 0, it);
        float fk[16];
#pragma unroll
        for (int k = 0; k < 16; k += 4) {
            const float4 u = lds128f(sb + SM_RED + (b * 256 + 128 + mg * 16 + k) * 4);
            fk[k] = u.x; fk[k + 1] = u.y; fk[k + 2] = u.z; fk[k + 3] = u.w;
        }
#pragma unroll 1
        while (true) {
            uint32_t bad = 0;
#pragma unroll
            for (int k = 0; k < 16; k++) bad |= bad_2x64(v[k], tag);
            if (!__any_sync(~0u, bad) || ++it >= SPIN_LIMIT) break;
            if (!late) __nanosleep(300);
#pragma unroll
            for (int k = 0; k < 16; k++) ld_2x64(v[k], row + k * (OROW / 4), bad_2x64(v[k], tag));
        }
        float4 acc = make_float4(0.f, 0.f, 0.f, 0.f), acd = acc;
#pragma unroll
        for (int k = 0; k < 16; k += 2) {
            const float4 x = val_2x64(v[k]), y = val_2x64(v[k + 1]);
            acc.x = fmaf(fk[k], x.x, acc.x); acc.y = fmaf(fk[k], x.y, acc.y); acc.z = fmaf(fk[k], x.z, acc.z); acc.w = fmaf(fk[k], x.w, acc.w);
            acd.x = fmaf(fk[k + 1], y.x, acd.x); acd.y = fmaf(fk[k + 1], y.y, acd.y); acd.z = fmaf(fk[k + 1], y.z, acd.z); acd.w = fmaf(fk[k + 1], y.w, acd.w);
        }
        acc.x += acd.x; acc.y += acd.y; acc.z += acd.z; acc.w += acd.w;
        acc.x += __shfl_xor_sync(~0u, acc.x, 16); acc.y += __shfl_xor_sync(~0u, acc.y, 16);
        acc.z += __shfl_xor_sync(~0u, acc.z, 16); acc.w += __shfl_xor_sync(~0u, acc.w, 16);
        if (lane < 12) reinterpret_cast<float4*>(part + (ht >> 5) * 48)[lane] = acc;
        __syncwarp();
        bar_sync(5 + b, 64);
        if (ht < 48) {
            const int dim = (ht & 48) + ((ht >> 1) & 7) + 8 * (ht & 1);
            const __nv_bfloat16 o = __float2bfloat16_rn(part[ht] + part[48 + ht]);
            if (latec) reinterpret_cast<__nv_bfloat16*>(s_co)[b * 48 + dim] = o;
            else s_co[dim * 2 + b] = __bfloat162float(o);
        }
        __syncwarp();
        if (lane == 0) mbar_arrive(bar_oc);
        if (fc < 40) {
            const int xt = tid - 352;
            uint4 hv[6];
#pragma unroll
            for (int i = 0; i < 6; i++) hv[i] = make_uint4(0, 0, 0, 0);
#pragma unroll 1
            while (true) {
#pragma unroll
                for (int i = 0; i < 6; i++) ld_pkt(hv[i], g_hh + xt + i * 128, bad_pkt(hv[i], tag));
                bool bad = false;
#pragma unroll
                for (int i = 0; i < 6; i++) bad |= bad_pkt(hv[i], tag);
                if (!__any_sync(~0u, bad) || ++it >= SPIN_LIMIT) break;
                __nanosleep(300);
            }
#pragma unroll
            for (int i = 0; i < 6; i++)
                reinterpret_cast<uint2*>(smem + SM_HH)[xt + i * 128] =
                    make_uint2(__byte_perm(hv[i].x, hv[i].y, 0x7632), __byte_perm(hv[i].z, hv[i].w, 0x7632));
            bar_sync(7, 128);
            float a0[8], a1[8];
#pragma unroll
            for (int e = 0; e < 8; e++) { a0[e] = 0.f; a1[e] = 0.f; }
            const int row = (warp - 11) * 64 + (lane >> 1);
#pragma unroll
            for (int i = 0; i < NW2; i++) {
                const int v = NT + i;
                uint32_t hh[4];
#pragma unroll
                for (int k = 0; k < 4; k++) hh[k] = lds32(sb + SM_HH + (i * 256 + row + k * 16) * 4);
                if (i == 0) mbar_sleep(bar_w2, it); else mbar_wait(bar_w2 + 8 * i, 0, it);
                uint4 w[4];
#pragma unroll
                for (int k = 0; k < 4; k++) w[k] = lds128(sb + SM_RING + (v & (NS - 1)) * TILE + (row + k * 16) * 32 + (lane & 1) * 16);
#pragma unroll
                for (int k = 0; k < 4; k++) {
                    const float h0 = bf_lo(hh[k]), h1 = bf_hi(hh[k]);
                    const uint32_t uw[4] = {w[k].x, w[k].y, w[k].z, w[k].w};
#pragma unroll
                    for (int e = 0; e < 4; e++) {
                        const float lo = bf_lo(uw[e]), hi = bf_hi(uw[e]);
                        a0[2 * e] = fmaf(lo, h0, a0[2 * e]); a0[2 * e + 1] = fmaf(hi, h0, a0[2 * e + 1]);
                        a1[2 * e] = fmaf(lo, h1, a1[2 * e]); a1[2 * e + 1] = fmaf(hi, h1, a1[2 * e + 1]);
                    }
                }
            }
            float r8[8], r4[4], r2[2];
#pragma unroll
            for (int e = 0; e < 8; e++) r8[e] = ((lane & 16) ? a1[e] : a0[e]) + __shfl_xor_sync(~0u, (lane & 16) ? a0[e] : a1[e], 16);
#pragma unroll
            for (int e = 0; e < 4; e++) r4[e] = ((lane & 8) ? r8[e + 4] : r8[e]) + __shfl_xor_sync(~0u, (lane & 8) ? r8[e] : r8[e + 4], 8);
#pragma unroll
            for (int e = 0; e < 2; e++) r2[e] = ((lane & 4) ? r4[e + 2] : r4[e]) + __shfl_xor_sync(~0u, (lane & 4) ? r4[e] : r4[e + 2], 4);
            const float r1 = ((lane & 2) ? r2[1] : r2[0]) + __shfl_xor_sync(~0u, (lane & 2) ? r2[0] : r2[1], 2);
            const int col = (lane & 1) * 8 + ((lane >> 1) & 7);
            reinterpret_cast<float*>(smem + SM_GP)[((lane & 16) + (col & 1) * 8 + (col >> 1)) * 4 + (warp - 11)] = r1;
            __syncwarp();
            bar_arrive(8, 160);
        }
        return;
    }
    if (warp >= 8) {
        tag = next_tag();
        bar_sync(1, NTHR);
        const int b = warp - 8;
        const float* src = g_o + (((grp * 32 + own2 + b) * 4 + j) * 64 + lane) * OROW + 48;
        const bool late = own2 + b >= LATE;
        mbar_sleep(go_o + 8 * b, it);
        if (!late) __nanosleep(EARLY_NS);
        uint2 s0 = make_uint2(0, 0), s1 = s0;
#pragma unroll 1
        while (true) {
            const uint2 t0 = take2(src, (s0.x & 3u) != tag), t1 = take2(src + 32 * OROW, (s1.x & 3u) != tag);
            if ((t0.x & 3u) == tag) s0 = t0;
            if ((t1.x & 3u) == tag) s1 = t1;
            if (!__any_sync(~0u, ((s0.x ^ tag) | (s1.x ^ tag)) & 3u) || ++it >= SPIN_LIMIT) break;
            if (!late) __nanosleep(300);
        }
        const float m0 = bf_hi(s0.x), m1 = bf_hi(s1.x);
        float m = fmaxf(m0, m1);
#pragma unroll
        for (int o = 16; o; o >>= 1) m = fmaxf(m, __shfl_xor_sync(~0u, m, o));
        const float f0 = __expf(m0 - m), f1 = __expf(m1 - m);
        float l = f0 * __uint_as_float(s0.y) + f1 * __uint_as_float(s1.y);
#pragma unroll
        for (int o = 16; o; o >>= 1) l += __shfl_xor_sync(~0u, l, o);
        float* wt = reinterpret_cast<float*>(smem + SM_RED) + b * 256 + 128;
        wt[lane] = __fdividef(f0, l);
        wt[32 + lane] = __fdividef(f1, l);
        __syncwarp();
        if (lane == 0) mbar_arrive(bar_wt + 8 * b);
    } else {
        const int g = lane >> 3, jj = lane & 7;
        const uint32_t pbase = sb + SM_P + warp * 256;
        {
            uint2 xr[2][5];
#pragma unroll
            for (int b = 0; b < 2; b++)
#pragma unroll
                for (int k = 0; k < 5; k++)
                    xr[b][k] = __ldg(reinterpret_cast<const uint2*>(p.x + b * D) + lane + 32 * k);
            const int row = jj < 5 ? 160 * j + 32 * jj + 4 * warp + g
                                   : (jj < 7 && warp < 5 ? 40 * (c >> 3) + 20 * (jj - 5) + 4 * warp + g : 0);
            const float x0 = __bfloat162float(p.x[row]), x1 = __bfloat162float(p.x[D + row]);
            tag = next_tag();
            float mean[2], den[2];
#pragma unroll
            for (int b = 0; b < 2; b++) {
                float s = 0.f;
#pragma unroll
                for (int k = 0; k < 5; k++)
                    s += (bf_lo(xr[b][k].x) + bf_hi(xr[b][k].x)) + (bf_lo(xr[b][k].y) + bf_hi(xr[b][k].y));
                mean[b] = s;
            }
#pragma unroll
            for (int o = 16; o; o >>= 1) {
                mean[0] += __shfl_xor_sync(~0u, mean[0], o);
                mean[1] += __shfl_xor_sync(~0u, mean[1], o);
            }
#pragma unroll
            for (int b = 0; b < 2; b++) {
                mean[b] *= (1.f / D);
                float s = 0.f;
#pragma unroll
                for (int k = 0; k < 5; k++) {
                    const float d0 = bf_lo(xr[b][k].x) - mean[b], d1 = bf_hi(xr[b][k].x) - mean[b];
                    const float d2 = bf_lo(xr[b][k].y) - mean[b], d3 = bf_hi(xr[b][k].y) - mean[b];
                    s = fmaf(d0, d0, fmaf(d1, d1, fmaf(d2, d2, fmaf(d3, d3, s))));
                }
                den[b] = s;
            }
#pragma unroll
            for (int o = 16; o; o >>= 1) {
                den[0] += __shfl_xor_sync(~0u, den[0], o);
                den[1] += __shfl_xor_sync(~0u, den[1], o);
            }
#pragma unroll
            for (int b = 0; b < 2; b++) {
                float sq;
                asm("sqrt.approx.f32 %0, %1;" : "=f"(sq) : "f"(rbf(rbf(den[b] * (1.f / D)) + 1e-5f)));
                den[b] = rbf(sq);
                mean[b] = rbf(mean[b]);
            }
            reinterpret_cast<float2*>(smem + SM_P + warp * 256)[jj * 4 + g] =
                make_float2(rbf(__fdividef(rbf(x0 - mean[0]), den[0])), rbf(__fdividef(rbf(x1 - mean[1]), den[1])));
        }
        bar_sync(1, NTHR);
        const uint32_t wordoff = sb + SM_RING + warp * 4 * 384 + lane * 4;
#pragma unroll
        for (int kind = 0; kind < 2; kind++) {
            float acc[12];
#pragma unroll
            for (int e = 0; e < 12; e++) acc[e] = 0.f;
#pragma unroll 1
            for (int v = kind ? V_W1 : V_WQ; v < (kind ? V_K : V_W1); v++) {
                const float4 c01 = lds128f(pbase + v * 32), c23 = lds128f(pbase + v * 32 + 16);
                const float cf[8] = {c01.x, c01.y, c01.z, c01.w, c23.x, c23.y, c23.z, c23.w};
                mbar_wait(full0 + 8 * v, 0, it);
                if (kind == 0 || warp < 5) {
                    uint32_t w[12];
#pragma unroll
                    for (int e = 0; e < 12; e++) w[e] = lds32(wordoff + v * TILE + e * 128);
#pragma unroll
                    for (int e = 0; e < 12; e++) {
                        const int r = e / 3, k = e - r * 3;
                        const float lo = bf_lo(w[e]), hi = bf_hi(w[e]);
                        acc[4 * k]     = fmaf(lo, cf[2 * r], acc[4 * k]);
                        acc[4 * k + 1] = fmaf(lo, cf[2 * r + 1], acc[4 * k + 1]);
                        acc[4 * k + 2] = fmaf(hi, cf[2 * r], acc[4 * k + 2]);
                        acc[4 * k + 3] = fmaf(hi, cf[2 * r + 1], acc[4 * k + 3]);
                    }
                }
                __syncwarp();
                if (lane == 0) mbar_arrive(empty0 + 8 * v);
            }
            float4* red = reinterpret_cast<float4*>(smem + SM_RED) + kind * (8 * 96);
#pragma unroll
            for (int k = 0; k < 3; k++)
                red[warp * 96 + lane + 32 * k] = make_float4(acc[4 * k], acc[4 * k + 1], acc[4 * k + 2], acc[4 * k + 3]);
            bar_sync(2, 256);
            const int u = tid - kind * 96;
            if (u >= 0 && u < 96) {
                float4 s = red[u];
#pragma unroll
                for (int w = 1; w < 8; w++) {
                    const float4 t = red[w * 96 + u];
                    s.x += t.x; s.y += t.y; s.z += t.z; s.w += t.w;
                }
                if (kind) st_tag4(g_h + c * 96 + u, s, tag); else st_pkt(g_q + c * 96 + u, s, tag);
            }
            __syncwarp();
        }
        bar_sync(3, 256);
        if (tid == 0) mbar_arrive(go_q);
        const uint32_t ks = (V_K + 2 * warp) & (NS - 1), vs = (V_K + 1 + 2 * warp) & (NS - 1);
        const int qg = lane >> 2, qt = lane & 3;
        const int krow = lane & 15, khi = lane >> 4, vrow = (lane & 7) + (lane >> 4) * 8, vhi = (lane >> 3) & 1;
        const uint32_t ooff = qt * (64 * OROW * 4) + qg * 8;
        const uint32_t osta = (lane >> 2) * (64 * OROW * 4) + 192 + (lane & 3) * 8;
#pragma unroll 1
        for (int s = warp; s < 32; s += 8) {
            char* ob = reinterpret_cast<char*>(g_o + ((grp * 32 + s) * 4 * 64 + mem) * OROW);
            if (s + 8 >= LATE && s + 8 < 32) {
                char* pb = ob + 8 * 4 * 64 * OROW * 4;
#pragma unroll
                for (int k = 0; k < 3; k++) st_64(pb + ooff + k * 64, 0, 0);
                if (lane < 16) st_64(pb + osta, 0, 0);
            }
            const uint32_t swm = s ? 7 : 0;
            uint32_t ka[3], va[3];
#pragma unroll
            for (int sg = 0; sg < 3; sg++) {
                const uint32_t lk = 3 * krow + sg, lv = 3 * vrow + sg;
                ka[sg] = sb + SM_RING + ks * TILE + lk * 128 + ((khi ^ (lk & swm)) << 4);
                va[sg] = sb + SM_RING + vs * TILE + lv * 128 + ((vhi ^ (lv & swm)) << 4);
            }
            uint32_t q[24];
            mbar_wait(qbar0 + 8 * (s >> 1), 0, it);
#pragma unroll
            for (int k = 0; k < 6; k++) {
                const uint4 u = lds128(sb + SM_Q + s * 384 + qt * 96 + k * 16);
                q[4 * k] = u.x; q[4 * k + 1] = u.y; q[4 * k + 2] = u.z; q[4 * k + 3] = u.w;
            }
            mbar_wait(full0 + 8 * ks, ((V_K + 2 * s) / NS) & 1, it);
            float4 sa[2][3];
#pragma unroll
            for (int i = 0; i < 6; i++) sa[i / 3][i % 3] = make_float4(0.f, 0.f, 0.f, 0.f);
#pragma unroll
            for (int kk = 0; kk < 4; kk++)
#pragma unroll
                for (int sg = 0; sg < 3; sg++)
#pragma unroll
                    for (int mb = 0; mb < 2; mb++) {
                        uint32_t a[4];
                        ldsm4(a, (ka[sg] ^ (kk << 5)) + mb * (48 * 128));
                        mma16(sa[mb][sg], a, q[sg * 8 + 2 * kk], q[sg * 8 + 2 * kk + 1]);
                    }
            __syncwarp();
            if (lane == 0) mbar_arrive_n(empty0 + 8 * ks, 8);
            float sc[4] = {(sa[0][0].x + sa[0][1].x) + sa[0][2].x, (sa[0][0].z + sa[0][1].z) + sa[0][2].z,
                           (sa[1][0].x + sa[1][1].x) + sa[1][2].x, (sa[1][0].z + sa[1][1].z) + sa[1][2].z};
#pragma unroll
            for (int i = 0; i < 4; i++) sc[i] = rbf(rbf(sc[i]) * 0.07216878364870322f);
            float m = fmaxf(fmaxf(sc[0], sc[1]), fmaxf(sc[2], sc[3]));
#pragma unroll
            for (int o = 16; o >= 4; o >>= 1) m = fmaxf(m, __shfl_xor_sync(~0u, m, o));
#pragma unroll
            for (int i = 0; i < 4; i++) sc[i] = __expf(sc[i] - m);
            float l = (sc[0] + sc[1]) + (sc[2] + sc[3]);
#pragma unroll
            for (int o = 16; o >= 4; o >>= 1) l += __shfl_xor_sync(~0u, l, o);
            if (lane < 16) st_64(ob + osta, tagw(m, tag), __float_as_uint(l));
            if (lane == 0 && (s & ~1) == own2) mbar_arrive(go_o + 8 * (s & 1));
            uint32_t pb0[2], pb1[2];
#pragma unroll
            for (int i = 0; i < 2; i++) {
                const __nv_bfloat162 pk = __floats2bfloat162_rn(sc[2 * i], sc[2 * i + 1]);
                const uint32_t w = *reinterpret_cast<const uint32_t*>(&pk);
                const uint32_t x = __shfl_sync(~0u, w, 8 * qt), y = __shfl_sync(~0u, w, 8 * qt + 4);
                pb0[i] = __byte_perm(x, y, 0x5410);
                pb1[i] = __byte_perm(x, y, 0x7632);
            }
            mbar_wait(full0 + 8 * vs, ((V_K + 1 + 2 * s) / NS) & 1, it);
            if (s == 31 && lane == 0) mbar_arrive(go_end);
            float4 oa[12];
#pragma unroll
            for (int mb = 0; mb < 12; mb++) {
                oa[mb] = make_float4(0.f, 0.f, 0.f, 0.f);
#pragma unroll
                for (int i = 0; i < 2; i++) {
                    uint32_t a[4];
                    ldsm4t(a, (va[mb >> 2] ^ ((mb & 3) << 5)) + i * (48 * 128));
                    mma16(oa[mb], a, pb0[i], pb1[i]);
                }
            }
#pragma unroll
            for (int k = 0; k < 3; k++) {
                const float lo = qt == 0 ? oa[k].x : qt == 1 ? oa[3 + k].x : qt == 2 ? oa[6 + k].x : oa[9 + k].x;
                const float hi = qt == 0 ? oa[k].z : qt == 1 ? oa[3 + k].z : qt == 2 ? oa[6 + k].z : oa[9 + k].z;
                st_64(ob + ooff + k * 64, tagw(lo, tag), __float_as_uint(hi));
            }
            __syncwarp();
            if (lane == 0) {
                mbar_arrive_n(empty0 + 8 * vs, 8);
                if ((s & ~1) == own2) mbar_arrive(go_v + 8 * (s & 1));
            }
        }
    }
    mbar_sleep(go_end, it);

    auto fma2 = [](float4& a, uint32_t w0, uint32_t w1, const float4& cf) {
        a.x = fmaf(bf_lo(w0), cf.x, a.x); a.y = fmaf(bf_hi(w0), cf.x, a.y);
        a.z = fmaf(bf_lo(w0), cf.y, a.z); a.w = fmaf(bf_hi(w0), cf.y, a.w);
        a.x = fmaf(bf_lo(w1), cf.z, a.x); a.y = fmaf(bf_hi(w1), cf.z, a.y);
        a.z = fmaf(bf_lo(w1), cf.w, a.z); a.w = fmaf(bf_hi(w1), cf.w, a.w);
    };
    const uint32_t wbase = sb + SM_RING + tid * 4;
    float4 acc = make_float4(0.f, 0.f, 0.f, 0.f), acc2 = acc;
    uint32_t w[44];
    mbar_wait(bar_ph, 0, it);
    constexpr int VL = NT - 1, SL = VL & (NS - 1), PL = (VL / NS) & 1;
    uint32_t wal = wbase + SL * TILE, fin = sb + SM_FIN + lane * 32 + warp * 4;
    const float4* pub = g_sp + c * 320 + tid;
    const float4* ps = g_sp + (tid >> 3) * 320 + 8 * fc + (tid & 7);
    uint32_t role = fc < 40 && warp < 8;
    pin(wal); pin(fin); pin(pub); pin(ps); pin(role);
    if (latec) {
        const uint32_t line = sb + SM_RING + (warp * 8 + (lane & 7)) * 128, wa = line + (((lane >> 3) ^ ((line >> 7) & 7)) << 4);
        uint32_t a[6][2][4];
        auto frag = [&](int t) {
            const uint32_t ad = wa + ((V_WO + t) & (NS - 1)) * TILE;
            ldsm4t(a[t][0], ad);
            ldsm4t(a[t][1], ad ^ 64);
        };
#pragma unroll
        for (int t = 0; t < 5; t++) {
            mbar_wait(full0 + 8 * ((V_WO + t) & (NS - 1)), ((V_WO + t) / NS) & 1, it);
            frag(t);
        }
        const bool early = __all_sync(~0u, mbar_test(full0 + 8 * (V_WS & (NS - 1)), (V_WS / NS) & 1));
        if (early) frag(5);
        pub = g_sp + c * 320 + warp * 32 + (lane >> 3) + (lane & 4);
        pin(pub);
        mbar_wait(bar_oc, 0, it);
        uint32_t b[6];
#pragma unroll
        for (int t = 0; t < 6; t++) b[t] = lane < 8 ? lds32(sb + SM_CO + (lane >> 2) * 96 + (lane & 3) * 4 + t * 16) : 0u;
        float4 d[4];
#pragma unroll
        for (int m = 0; m < 4; m++) d[m] = make_float4(0.f, 0.f, 0.f, 0.f);
#pragma unroll
        for (int t = 0; t < 6; t++) {
            if (t == 5 && !early) {
                mbar_wait(full0 + 8 * (V_WS & (NS - 1)), (V_WS / NS) & 1, it);
                frag(5);
            }
#pragma unroll
            for (int m = 0; m < 4; m++) mma8(d[m], a[t][m >> 1][(m & 1) * 2], a[t][m >> 1][(m & 1) * 2 + 1], b[t]);
        }
        const bool odd = lane & 4;
#pragma unroll
        for (int m = 0; m < 4; m++) {
            const float x = __shfl_xor_sync(~0u, odd ? d[m].x : d[m].z, 4), y = __shfl_xor_sync(~0u, odd ? d[m].y : d[m].w, 4);
            if ((lane & 3) == 0) st_pkt(pub + m * 8, odd ? make_float4(x, d[m].z, y, d[m].w) : make_float4(d[m].x, x, d[m].y, y), tag);
        }
    } else {
#pragma unroll
        for (int t = 0; t < 3; t++) {
            const int v = V_WO + t, slot = v & (NS - 1);
            mbar_wait(full0 + 8 * slot, (v / NS) & 1, it);
#pragma unroll
            for (int r = 0; r < 8; r++) w[t * 8 + r] = lds32(wbase + slot * TILE + r * 1280);
        }
        mbar_wait(bar_oc, 0, it);
#pragma unroll
        for (int r = 0; r < 24; r += 2) fma2((r & 2) ? acc2 : acc, w[r], w[r + 1], lds128f(sb + SM_CO + r * 8));
#pragma unroll
        for (int v = V_WO + 3; v < VL; v++) {
            const int slot = v & (NS - 1), r0 = (v - V_WO) * 8, nr = v < V_WS ? 8 : 4;
            mbar_wait(full0 + 8 * slot, (v / NS) & 1, it);
#pragma unroll
            for (int r = 0; r < nr; r++) w[r0 + r] = lds32(wbase + slot * TILE + r * 1280);
#pragma unroll
            for (int r = r0; r < r0 + nr; r += 2) fma2((r & 2) ? acc2 : acc, w[r], w[r + 1], lds128f(sb + SM_CO + r * 8));
        }
        {
            const float4 c0 = lds128f(sb + SM_CO + 44 * 8), c1 = lds128f(sb + SM_CO + 46 * 8);
            acc.x += acc2.x; acc.y += acc2.y; acc.z += acc2.z; acc.w += acc2.w;
            mbar_wait(full0 + 8 * SL, PL, it);
            const uint32_t w0 = lds32(wal), w1 = lds32(wal + 1280), w2 = lds32(wal + 2560), w3 = lds32(wal + 3840);
            acc2 = make_float4(0.f, 0.f, 0.f, 0.f);
            fma2(acc, w0, w1, c0);
            fma2(acc2, w2, w3, c1);
            st_pkt(pub, make_float4(acc.x + acc2.x, acc.y + acc2.y, acc.z + acc2.z, acc.w + acc2.w), tag);
        }
    }
    __syncwarp();
    if (role) {
        uint4 sv[4];
#pragma unroll
        for (int k = 0; k < 4; k++) sv[k] = make_uint4(0, 0, 0, 0);
#pragma unroll 1
        do {
#pragma unroll
            for (int k = 0; k < 4; k++) ld_pkt(sv[k], ps + k * 32 * 320, bad_pkt(sv[k], tag));
        } while (__any_sync(~0u, bad_pkt(sv[0], tag) | bad_pkt(sv[1], tag) | bad_pkt(sv[2], tag) | bad_pkt(sv[3], tag)) && ++it < SPIN_LIMIT);
        const float4 u = pkt_val(sv[0]), w = pkt_val(sv[1]), y = pkt_val(sv[2]), z = pkt_val(sv[3]);
        const float4 a = make_float4((u.x + w.x) + (y.x + z.x), (u.y + w.y) + (y.y + z.y), (u.z + w.z) + (y.z + z.z), (u.w + w.w) + (y.w + z.w));
        const bool h4 = lane & 16, h3 = lane & 8;
        const float k0 = (h4 ? a.z : a.x) + __shfl_xor_sync(~0u, h4 ? a.x : a.z, 16);
        const float k1 = (h4 ? a.w : a.y) + __shfl_xor_sync(~0u, h4 ? a.y : a.w, 16);
        const float r = (h3 ? k1 : k0) + __shfl_xor_sync(~0u, h3 ? k0 : k1, 8);
        asm volatile("st.shared.f32 [%0], %1;" ::"r"(fin), "f"(r) : "memory");
        __syncwarp();
        bar_arrive(9, 288);
    }
}

typedef CUresult (*EncodeFn)(CUtensorMap*, CUtensorMapDataType, cuuint32_t, void*, const cuuint64_t*, const cuuint64_t*,
                             const cuuint32_t*, const cuuint32_t*, CUtensorMapInterleave, CUtensorMapSwizzle,
                             CUtensorMapL2promotion, CUtensorMapFloatOOBfill);

void encode_2d(EncodeFn fn, CUtensorMap* map, void* ptr, int cols, int rows, int box_cols, int box_rows,
               CUtensorMapL2promotion promo) {
    const cuuint64_t dims[2] = {(cuuint64_t)cols, (cuuint64_t)rows}, strides[1] = {(cuuint64_t)cols * 2};
    const cuuint32_t box[2] = {(cuuint32_t)box_cols, (cuuint32_t)box_rows}, es[2] = {1, 1};
    fn(map, CU_TENSOR_MAP_DATA_TYPE_BFLOAT16, 2, ptr, dims, strides, box, es, CU_TENSOR_MAP_INTERLEAVE_NONE,
       CU_TENSOR_MAP_SWIZZLE_NONE, promo, CU_TENSOR_MAP_FLOAT_OOB_FILL_NONE);
}

void encode_wo(EncodeFn fn, CUtensorMap* map, void* ptr) {
    const cuuint64_t dims[3] = {64, (cuuint64_t)QD, 10}, strides[2] = {(cuuint64_t)D * 2, 128};
    const cuuint32_t box[3] = {64, 8, 10}, es[3] = {1, 1, 1};
    fn(map, CU_TENSOR_MAP_DATA_TYPE_BFLOAT16, 3, ptr, dims, strides, box, es, CU_TENSOR_MAP_INTERLEAVE_NONE,
       CU_TENSOR_MAP_SWIZZLE_128B, CU_TENSOR_MAP_L2_PROMOTION_L2_128B, CU_TENSOR_MAP_FLOAT_OOB_FILL_NONE);
}

void encode_kv(EncodeFn fn, CUtensorMap* map, void* ptr) {
    const cuuint64_t dims[2] = {64, (cuuint64_t)2 * 32 * SK * 3}, strides[1] = {128};
    const cuuint32_t box[2] = {64, 96}, es[2] = {1, 1};
    fn(map, CU_TENSOR_MAP_DATA_TYPE_BFLOAT16, 2, ptr, dims, strides, box, es, CU_TENSOR_MAP_INTERLEAVE_NONE,
       CU_TENSOR_MAP_SWIZZLE_128B, CU_TENSOR_MAP_L2_PROMOTION_L2_128B, CU_TENSOR_MAP_FLOAT_OOB_FILL_NONE);
}

}

extern "C" void kernel_launch(void* const* d_in, const int* in_sizes, int n_in, void* d_out, int out_size) {
    (void)in_sizes; (void)n_in; (void)out_size;
    static EncodeFn encode = nullptr;
    static double peak_gbs = 3352.0;
    if (!encode) {
        void* fn = nullptr;
        cudaDriverEntryPointQueryResult qr;
        cudaGetDriverEntryPoint("cuTensorMapEncodeTiled", &fn, cudaEnableDefault, &qr);
        encode = (EncodeFn)fn;
        int dev = 0, khz = 0, bits = 0;
        cudaGetDevice(&dev);
        if (cudaDeviceGetAttribute(&khz, cudaDevAttrMemoryClockRate, dev) == cudaSuccess &&
            cudaDeviceGetAttribute(&bits, cudaDevAttrGlobalMemoryBusWidth, dev) == cudaSuccess && khz > 0 && bits > 0) {
            const double gbs = 2.0 * khz * (bits / 8) * 1e-6;
            if (gbs > 2500.0) peak_gbs = gbs;
        }
        cudaFuncSetAttribute(fused_decode_kernel, cudaFuncAttributeMaxDynamicSharedMemorySize, SM_TOTAL);
    }
    CUtensorMap map_wq, map_w1, map_k, map_v, map_wo, map_w2;
    encode_wo(encode, &map_wo, d_in[4]);
    encode_kv(encode, &map_k, d_in[1]);
    encode_kv(encode, &map_v, d_in[2]);
    encode_2d(encode, &map_wq, d_in[3], QD, D, DH, 32, CU_TENSOR_MAP_L2_PROMOTION_L2_128B);
    encode_2d(encode, &map_w1, d_in[6], FF, D, DH, 20, CU_TENSOR_MAP_L2_PROMOTION_L2_128B);
    encode_2d(encode, &map_w2, d_in[8], D, FF, 16, 256, CU_TENSOR_MAP_L2_PROMOTION_L2_64B);
    Params p;
    p.x  = (const __nv_bfloat16*)d_in[0];
    p.k  = (const __nv_bfloat16*)d_in[1];
    p.v  = (const __nv_bfloat16*)d_in[2];
    p.b1 = (const __nv_bfloat16*)d_in[7];
    p.b2 = (const __nv_bfloat16*)d_in[9];
    p.out = (__nv_bfloat16*)d_out;
    p.wo = (const __nv_bfloat16*)d_in[4];
    p.pace = (uint32_t)(256.0 * NCTA / (PACE_OF_PEAK * peak_gbs) * 65536.0);
    fused_decode_kernel<<<NCTA, NTHR, SM_TOTAL, cudaStreamPerThread>>>(map_wq, map_w1, map_k, map_v, map_wo, map_w2, p);
}
```
